```python
import torch

def _softmax(x, axis=-1):
    return torch.softmax(x, dim=axis)
def _gelu(x):
    return torch.nn.functional.gelu(x, approximate="tanh")
def _silu(x):
    return torch.nn.functional.silu(x)
def _sigmoid(x):
    return torch.sigmoid(x)
def _layernorm(x, axis=-1, eps=1e-5):
    m = x.mean(dim=axis, keepdim=True)
    v = x.var(dim=axis, keepdim=True, unbiased=False)
    return (x - m) / torch.sqrt(v + eps)
def _scatter_add(tgt, idx, src, axis=0):
    return tgt.clone().index_add_(axis, idx, src)
def _segment_sum(src, seg, n):
    out = torch.zeros((n,) + src.shape[1:], dtype=src.dtype)
    return out.index_add_(0, seg, src)
def _pad(x, pw):
    flat = tuple(v for pair in reversed(pw) for v in pair)
    return torch.nn.functional.pad(x, flat)

kernel_name = 'interleave_layers__sliding_block_cached__gqa_block_cached__decode'

def setup_inputs():

    _w = (lambda a: (lambda t: t.to(torch.bfloat16) if t.is_floating_point() else t)(torch.as_tensor(a)))
    def _A_setup():
        B, Sq, D = 2, 1, 640
        Hq, Hkv, Sk, Dh = 32, 32, 4096, 192
        assert Hq % Hkv == 0, (Hq, Hkv)
        return {
            "x": _w((lambda *s: torch.randn(*s, dtype=torch.bfloat16) * 0.1)(B, Sq, D)),
            "k_cache": _w((lambda *s: torch.randn(*s, dtype=torch.bfloat16) * 0.8)(B, Hkv, Sk, Dh)),
            "v_cache": _w((lambda *s: torch.randn(*s, dtype=torch.bfloat16) * 3.2)(B, Hkv, Sk, Dh)),
            "wq": _w((lambda *s: torch.randn(*s, dtype=torch.bfloat16) * 0.8)(D, Hq * Dh) * (D ** -0.5)),
            "wo": _w((lambda *s: torch.randn(*s, dtype=torch.bfloat16) * 3.2)(Hq * Dh, D) * ((Hq * Dh) ** -0.5)),
        }
    _A_in = _A_setup()

    def _B_setup():
        B, Sq, D = 2, 1, 640
        Hq, Hkv, Sk, Dh = 32, 32, 4096, 192
        assert Hq % Hkv == 0, (Hq, Hkv)
        return {
            "x": _w((lambda *s: torch.randn(*s, dtype=torch.bfloat16) * 0.1)(B, Sq, D)),
            "k_cache": _w((lambda *s: torch.randn(*s, dtype=torch.bfloat16) * 1.6)(B, Hkv, Sk, Dh)),
            "v_cache": _w((lambda *s: torch.randn(*s, dtype=torch.bfloat16) * 1.6)(B, Hkv, Sk, Dh)),
            "wq": _w((lambda *s: torch.randn(*s, dtype=torch.bfloat16) * 1.6)(D, Hq * Dh) * (D ** -0.5)),
            "wo": _w((lambda *s: torch.randn(*s, dtype=torch.bfloat16) * 1.6)(Hq * Dh, D) * ((Hq * Dh) ** -0.5)),
        }
    _B_in = _B_setup()

    return {
        "A_x": _A_in["x"],
        "A_k_cache": _A_in["k_cache"],
        "A_v_cache": _A_in["v_cache"],
        "A_wq": _A_in["wq"],
        "A_wo": _A_in["wo"],
        "B_x": _B_in["x"],
        "B_k_cache": _B_in["k_cache"],
        "B_v_cache": _B_in["v_cache"],
        "B_wq": _B_in["wq"],
        "B_wo": _B_in["wo"],
    }

def reference(A_x, A_k_cache, A_v_cache, A_wq, A_wo, B_x, B_k_cache, B_v_cache, B_wq, B_wo):
    def _A_ref(x, k_cache, v_cache, wq, wo):
        B, Sq, D = x.shape
        Hq, Dh = 32, 192
        Hkv, Sk = k_cache.shape[1], k_cache.shape[2]
        W = min(4096, max(256, Sk // 4))
        rep = Hq // Hkv
        q = (lambda x, *d: x.permute(*d))((x @ wq).reshape(B, Sq, Hq, Dh), 0, 2, 1, 3)
        k = (lambda x, n, axis: torch.repeat_interleave(x, n, dim=axis))(k_cache[:, :, Sk - W:, :], rep, axis=1)
        v = (lambda x, n, axis: torch.repeat_interleave(x, n, dim=axis))(v_cache[:, :, Sk - W:, :], rep, axis=1)
        scores = torch.einsum("bhqd,bhkd->bhqk", q, k) * (Dh ** -0.5)
        p = _softmax(scores, axis=-1)
        o = torch.einsum("bhqk,bhkd->bhqd", p, v)
        return (lambda x, *d: x.permute(*d))(o, 0, 2, 1, 3).reshape(B, Sq, Hq * Dh) @ wo

    def _B_ref(x, k_cache, v_cache, wq, wo):
        B, Sq, D = x.shape
        Hq, Dh = 32, 192
        Hkv = k_cache.shape[1]
        rep = Hq // Hkv
        q = (lambda x, *d: x.permute(*d))((x @ wq).reshape(B, Sq, Hq, Dh), 0, 2, 1, 3)
        k = (lambda x, n, axis: torch.repeat_interleave(x, n, dim=axis))(k_cache, rep, axis=1)
        v = (lambda x, n, axis: torch.repeat_interleave(x, n, dim=axis))(v_cache, rep, axis=1)
        scores = torch.einsum("bhqd,bhkd->bhqk", q, k) * (Dh ** -0.5)
        p = _softmax(scores, axis=-1)
        o = torch.einsum("bhqk,bhkd->bhqd", p, v)
        return (lambda x, *d: x.permute(*d))(o, 0, 2, 1, 3).reshape(B, Sq, Hq * Dh) @ wo

    x = A_x
    x = x + _A_ref(_layernorm(x, axis=-1), A_k_cache, A_v_cache, A_wq, A_wo)
    x = x + _B_ref(_layernorm(x, axis=-1), B_k_cache, B_v_cache, B_wq, B_wo)
    x = x + _A_ref(_layernorm(x, axis=-1), A_k_cache, A_v_cache, A_wq, A_wo)
    x = x + _B_ref(_layernorm(x, axis=-1), B_k_cache, B_v_cache, B_wq, B_wo)
    return x
```

```cpp
#include <cuda_runtime.h>
#include <cuda_bf16.h>
#include <cuda.h>
#include <stdint.h>

namespace {

constexpr int kCtas = 128;
constexpr int kThreads = 384;
constexpr int kSlotBytes = 3072;
constexpr int kRing = 3;
constexpr int kSlots = 9;
constexpr int kWRow = 196;

constexpr int kOffWbuf = kSlots * 8 * kSlotBytes;
constexpr int kOffCpart = kOffWbuf + 8 * kWRow * 4;
constexpr int kOffQf = kOffCpart + 2 * kWRow * 4;
constexpr int kOffXn = kOffQf + 2 * 96 * 4;
constexpr int kOffObf = kOffXn + 2 * 160 * 2;
constexpr int kOffFull = kOffObf + 2 * 48 * 2;
constexpr int kOffEmpty = kOffFull + 2 * kSlots * 8;
constexpr int kOffSync = kOffEmpty + 2 * kSlots * 8;
constexpr int kSmemBytes = kOffSync + 14 * 8;
static_assert(kSmemBytes <= 232448, "shared memory budget");
constexpr int kBarRows = 0, kBarFree = 8, kBarQ = 16, kBarXn = 32, kBarO = 48;
constexpr int kBarSentQ = 64, kBarSentP = 80, kBarSentY = 96;

constexpr int kMaxProg = 48;
constexpr int kMaxLoads = 200;

enum : uint32_t { OP_END = 0, OP_QPROJ = 1, OP_RFLOAD = 2, OP_SEG = 3, OP_OPROJ = 4 };
enum : uint32_t { LD_NONE = 0, LD_KEEP = 1u << 3, LD_LOW = 1u << 8, LD_VALID = 1u << 9, LD_PREFETCH = 1u << 30, LD_HIT = 1u << 31 };
enum : uint32_t { MG_END = 0, MG_ATTN = 1, MG_Q = 2 };

struct alignas(64) Params {
    CUtensorMap tm[8];
    const __nv_bfloat16* x;
    __nv_bfloat16* out;
    uint32_t winLow, winHigh;
    uint32_t tau, tauLow, tauW, credit;
    uint32_t exp;
    uint32_t keepAlive;
    uint32_t prog[kMaxProg];
    uint32_t merge[kMaxProg];
    uint32_t loads[kMaxLoads];
};

__device__ uint4 g_q[2][32][4][40];
__device__ uint4 g_p[2][32][4][4][18];
__device__ uint4 g_y[2][128][128][2];
__device__ uint4 g_x[2][128][2];

#define SPINNS 30
#define SLEEPNS 0
#define POLL_SLEEP
constexpr uint32_t kSpinLimit = 1u << 22;

__device__ __forceinline__ void mbar_init(uint32_t bar, uint32_t count) {
    asm volatile("mbarrier.init.shared::cta.b64 [%0], %1;" ::"r"(bar), "r"(count) : "memory");
}
__device__ __forceinline__ void mbar_arrive(uint32_t bar) {
    asm volatile("mbarrier.arrive.shared::cta.b64 _, [%0];" ::"r"(bar) : "memory");
}
__device__ __forceinline__ bool mbar_test(uint32_t bar, uint32_t parity) {
    uint32_t ok;
    asm volatile(
        "{\n\t.reg .pred p;\n\t"
        "mbarrier.test_wait.parity.shared::cta.b64 p, [%1], %2;\n\t"
        "selp.u32 %0, 1, 0, p;\n\t}"
        : "=r"(ok) : "r"(bar), "r"(parity) : "memory");
    return __all_sync(0xffffffffu, ok);
}
__device__ __forceinline__ void mbar_expect(uint32_t bar, uint32_t bytes) {
    asm volatile("mbarrier.arrive.expect_tx.shared::cta.b64 _, [%0], %1;" ::"r"(bar), "r"(bytes) : "memory");
}
__device__ __forceinline__ void mbar_wait(uint32_t bar, uint32_t parity) {
    uint32_t ok, it = 0;
    do {
        asm volatile(
            "{\n\t.reg .pred p;\n\t"
            "mbarrier.try_wait.parity.shared::cta.b64 p, [%1], %2;\n\t"
            "selp.u32 %0, 1, 0, p;\n\t}"
            : "=r"(ok) : "r"(bar), "r"(parity) : "memory");
        if (++it > kSpinLimit) __trap();
    } while (!ok);
}
__device__ __forceinline__ bool mbar_try(uint32_t bar, uint32_t parity) {
    uint32_t ok;
    asm volatile(
        "{\n\t.reg .pred p;\n\t"
        "mbarrier.try_wait.parity.shared::cta.b64 p, [%1], %2;\n\t"
        "selp.u32 %0, 1, 0, p;\n\t}"
        : "=r"(ok) : "r"(bar), "r"(parity) : "memory");
    return __all_sync(0xffffffffu, ok);
}
__device__ __forceinline__ void mbar_wait_u(uint32_t bar, uint32_t parity) {
    for (uint32_t it = 0; !mbar_try(bar, parity); it++)
        if (it > kSpinLimit) __trap();
}
__device__ __forceinline__ void prefetch_l2(const void* p) {
    asm volatile("prefetch.global.L2 [%0];" ::"l"(p) : "memory");
}
__device__ __forceinline__ void tma3d(uint32_t dst, const CUtensorMap* tm, int c0, int c1, int c2, uint32_t bar, uint64_t pol) {
    asm volatile(
        "cp.async.bulk.tensor.3d.shared::cluster.global.mbarrier::complete_tx::bytes.L2::cache_hint "
        "[%0], [%1, {%2, %3, %4}], [%5], %6;"
        ::"r"(dst), "l"(tm), "r"(c0), "r"(c1), "r"(c2), "r"(bar), "l"(pol) : "memory");
}
__device__ __forceinline__ void tma3d_prefetch(const CUtensorMap* tm, int c0, int c1, int c2, uint64_t pol) {
    asm volatile("cp.async.bulk.prefetch.tensor.3d.L2.global.L2::cache_hint [%0, {%1, %2, %3}], %4;"
                 ::"l"(tm), "r"(c0), "r"(c1), "r"(c2), "l"(pol) : "memory");
}
__device__ __forceinline__ uint64_t make_policy(bool keep) {
    uint64_t pol;
    if (keep) asm volatile("createpolicy.fractional.L2::evict_normal.b64 %0, 1.0;" : "=l"(pol));
    else      asm volatile("createpolicy.fractional.L2::evict_first.b64 %0, 1.0;" : "=l"(pol));
    return pol;
}
__device__ __forceinline__ void ldsm4(uint32_t (&r)[4], uint32_t addr) {
    asm volatile("ldmatrix.sync.aligned.m8n8.x4.shared.b16 {%0,%1,%2,%3}, [%4];"
                 : "=r"(r[0]), "=r"(r[1]), "=r"(r[2]), "=r"(r[3]) : "r"(addr) : "memory");
}
__device__ __forceinline__ void ldsm4t(uint32_t (&r)[4], uint32_t addr) {
    asm volatile("ldmatrix.sync.aligned.m8n8.x4.trans.shared.b16 {%0,%1,%2,%3}, [%4];"
                 : "=r"(r[0]), "=r"(r[1]), "=r"(r[2]), "=r"(r[3]) : "r"(addr) : "memory");
}
__device__ __forceinline__ void mma16816(float (&c)[4], const uint32_t (&a)[4], uint32_t b0, uint32_t b1) {
    asm volatile("mma.sync.aligned.m16n8k16.row.col.f32.bf16.bf16.f32 {%0,%1,%2,%3}, {%4,%5,%6,%7}, {%8,%9}, {%0,%1,%2,%3};"
                 : "+f"(c[0]), "+f"(c[1]), "+f"(c[2]), "+f"(c[3])
                 : "r"(a[0]), "r"(a[1]), "r"(a[2]), "r"(a[3]), "r"(b0), "r"(b1));
}
__device__ __forceinline__ float bf16r(float v) { return __bfloat162float(__float2bfloat16_rn(v)); }
__device__ __forceinline__ uint32_t pack_bf16(float lo, float hi) {
    uint32_t r;
    asm("cvt.rn.bf16x2.f32 %0, %1, %2;" : "=r"(r) : "f"(hi), "f"(lo));
    return r;
}
__device__ __forceinline__ bool elect() {
    uint32_t p;
    asm volatile("{\n\t.reg .pred e;\n\telect.sync _|e, 0xffffffff;\n\tselp.u32 %0, 1, 0, e;\n\t}" : "=r"(p));
    return p;
}
__device__ __forceinline__ float fast_sqrt(float v) {
    float r;
    asm("sqrt.approx.f32 %0, %1;" : "=f"(r) : "f"(v));
    return r;
}
__device__ __forceinline__ float ex2(float v) {
    float r;
    asm("ex2.approx.ftz.f32 %0, %1;" : "=f"(r) : "f"(v));
    return r;
}
__device__ __forceinline__ void st_packet(uint4* p, uint32_t a, uint32_t b, uint32_t c, uint32_t tag) {
    asm volatile(
        "{\n\t.reg .b64 lo, hi;\n\t.reg .b128 v;\n\t"
        "mov.b64 lo, {%1, %2};\n\tmov.b64 hi, {%3, %4};\n\tmov.b128 v, {lo, hi};\n\t"
        "st.relaxed.gpu.global.b128 [%0], v;\n\t}"
        ::"l"(p), "r"(a), "r"(b), "r"(c), "r"(tag) : "memory");
}
__device__ __forceinline__ void st_packet(uint4* p, float a, float b, float c, uint32_t tag) {
    st_packet(p, __float_as_uint(a), __float_as_uint(b), __float_as_uint(c), tag);
}
__device__ __forceinline__ uint4 ld_packet(const uint4* p) {
    uint4 v;
    asm volatile(
        "{\n\t.reg .b64 lo, hi;\n\t.reg .b128 v;\n\t"
        "ld.relaxed.gpu.global.b128 v, [%4];\n\t"
        "mov.b128 {lo, hi}, v;\n\tmov.b64 {%0, %1}, lo;\n\tmov.b64 {%2, %3}, hi;\n\t}"
        : "=r"(v.x), "=r"(v.y), "=r"(v.z), "=r"(v.w) : "l"(p) : "memory");
    return v;
}
#define POLL_UNTIL(loads, done)                 \
    for (uint32_t it_ = 0;; it_++) {            \
        loads;                                  \
        if (__all_sync(0xffffffffu, done)) break; \
        if (it_ > kSpinLimit) __trap();         \
        POLL_SLEEP;                             \
    }
__device__ __forceinline__ uint32_t round24(float v) {
    const uint32_t u = __float_as_uint(v);
    return u + ((u & 0x7f800000u) == 0x7f800000u ? 0u : 0x80u);
}
__device__ __forceinline__ void st_packet5(uint4* p, const float* v, uint32_t tag) {
    const uint32_t r0 = round24(v[0]), r1 = round24(v[1]), r2 = round24(v[2]), r3 = round24(v[3]), r4 = round24(v[4]);
    st_packet(p, __byte_perm(r0, r1, 0x5321), __byte_perm(r1, r2, 0x6532), __byte_perm(r2, r3, 0x7653),
              (r4 >> 8) | (tag << 24));
}
__device__ __forceinline__ void add_packet5(float (&a)[5], const uint4& v) {
    a[0] += __uint_as_float(v.x << 8);
    a[1] += __uint_as_float(__funnelshift_r(v.x, v.y, 16) & 0xffffff00u);
    a[2] += __uint_as_float(__funnelshift_r(v.y, v.z, 8) & 0xffffff00u);
    a[3] += __uint_as_float(v.z & 0xffffff00u);
    a[4] += __uint_as_float(v.w << 8);
}
__device__ __forceinline__ uint32_t now_ns() {
    uint32_t t;
    asm volatile("mov.u32 %0, %globaltimer_lo;" : "=r"(t));
    return t;
}
__device__ __forceinline__ float bf_lo(uint32_t v) { return __uint_as_float(v << 16); }
__device__ __forceinline__ float bf_hi(uint32_t v) { return __uint_as_float(v & 0xffff0000u); }
__device__ __forceinline__ float warp_sum(float v) {
#pragma unroll
    for (int o = 16; o > 0; o >>= 1) v += __shfl_xor_sync(0xffffffffu, v, o);
    return v;
}

constexpr float kLog2e = 1.4426950408889634f;
constexpr float kScale = 0.07216878364870322f;

struct Attn {
    float m, l;
    float acc[3][4];
};

__device__ __forceinline__ float score(float dot) { return bf16r(bf16r(dot) * kScale); }

__device__ __forceinline__ uint32_t probability(Attn& st, float s) {
    const float e = ex2((s - st.m) * kLog2e);
    st.l += e;
    const float hi = bf16r(e);
    const uint32_t hl = pack_bf16(hi, e - hi);
    uint32_t pv;
    asm volatile("movmatrix.sync.aligned.m8n8.trans.b16 %0, %1;" : "=r"(pv) : "r"(hl));
    return pv;
}

__device__ __forceinline__ uint32_t softmax_step(Attn& st, float dot) {
    const float s = score(dot);
    if (__any_sync(0xffffffffu, s > st.m)) {
        float mx = fmaxf(s, __shfl_xor_sync(0xffffffffu, s, 4));
        mx = fmaxf(mx, __shfl_xor_sync(0xffffffffu, mx, 8));
        mx = fmaxf(mx, __shfl_xor_sync(0xffffffffu, mx, 16));
        mx = fmaxf(mx, st.m);
        const float corr = ex2((st.m - mx) * kLog2e);
        st.m = mx;
        st.l *= corr;
#pragma unroll
        for (int a = 0; a < 3; a++)
#pragma unroll
            for (int i = 0; i < 4; i++) st.acc[a][i] *= corr;
    }
    return probability(st, s);
}

#define TRACE_G(i)

__global__ void __launch_bounds__(kThreads, 1)
fused_decode_kernel(const __grid_constant__ Params P) {
    extern __shared__ __align__(1024) unsigned char smem[];
    const uint32_t sbase = (uint32_t)__cvta_generic_to_shared(smem);
    const uint32_t sync0 = sbase + kOffSync;
    float* const wbuf = reinterpret_cast<float*>(smem + kOffWbuf);

    const int lane = threadIdx.x & 31;
    const int w = __shfl_sync(0xffffffffu, threadIdx.x >> 5, 0);
    const int cta = blockIdx.x;
    const int h = cta >> 2, jq = cta & 3;

    if (elect()) {
        if (w == 8) {
#pragma unroll
            for (int i = 0; i < 2 * kSlots; i++) mbar_init(sbase + kOffFull + 8 * i, 1);
        } else if (w == 9) {
#pragma unroll
            for (int i = 0; i < 2 * kSlots; i++) mbar_init(sbase + kOffEmpty + 8 * i, 4);
        } else if (w == 10) {
#pragma unroll
            for (int i = 0; i < 14; i++) mbar_init(sync0 + 8 * i, (8 * i == kBarRows || 8 * i >= kBarSentY) ? 8 : 1);
        }
        asm volatile("fence.mbarrier_init.release.cluster;" ::: "memory");
    }
    __syncthreads();

    if (w < 8) {
        asm volatile("setmaxnreg.inc.sync.aligned.u32 232;");
        const uint32_t slot0 = sbase + w * kSlotBytes;
        const uint32_t full0 = sbase + kOffFull + (w >> 2) * 8;

        uint32_t off[3];
#pragma unroll
        for (int u = 0; u < 3; u++) {
            const int line = 3 * (lane & 7) + u;
            off[u] = line * 128 + (((lane >> 3) ^ (line & 7)) << 4);
        }
        uint32_t par = 0, rpos = 0, nrows = 0;
        auto wait_tile = [&](uint32_t s) { mbar_wait(full0 + 16 * s, (par >> s) & 1u); };
        auto release = [&](uint32_t s) {
            par ^= 1u << s;
            __syncwarp();
            if (elect()) mbar_arrive(full0 + 16 * s + (kOffEmpty - kOffFull));
        };
        auto ring_release = [&]() {
            release(rpos);
            if (++rpos == kRing) rpos = 0;
        };
        auto row_acquire = [&]() { mbar_wait(sync0 + kBarFree, (nrows & 1) ^ 1); };
        auto row_publish = [&]() {
            __syncwarp();
            if (elect()) mbar_arrive(sync0 + kBarRows);
            nrows++;
        };

        uint32_t rf[8][6][4];
#pragma unroll
        for (int i = 0; i < 8; i++)
#pragma unroll
            for (int s = 0; s < 6; s++)
#pragma unroll
                for (int k = 0; k < 4; k++) rf[i][s][k] = 0;

#pragma unroll 1
        for (int pc = 0;; pc++) {
            const uint32_t op = P.prog[pc];
            const uint32_t kind = op & 7u;
            if (kind == OP_END) break;
            int lane = threadIdx.x & 31;
            asm volatile("" : "+r"(lane));
            const int g = lane >> 2, t = lane & 3;
            float* const row = wbuf + w * kWRow;

            if (kind == OP_SEG) {
                const uint32_t b = (op >> 3) & 1u;
                mbar_wait(sync0 + kBarQ + 8 * b, (op >> 4) & 1u);
                const uint2* qf = reinterpret_cast<const uint2*>(smem + kOffQf) + b * 48 + (lane & 7);
                Attn st;
                st.m = -INFINITY; st.l = 0.f;
#pragma unroll
                for (int a = 0; a < 3; a++)
#pragma unroll
                    for (int i = 0; i < 4; i++) st.acc[a][i] = 0.f;

                if (op & (1u << 7)) {
                    float c[4][4] = {};
#pragma unroll
                    for (int k = 0; k < 6; k++) {
                        const uint2 q = qf[8 * k];
#pragma unroll
                        for (int i = 0; i < 4; i++) mma16816(c[i], rf[2 * i][k], q.x, q.y);
                    }
                    float sc[4];
#pragma unroll
                    for (int i = 0; i < 4; i++) sc[i] = score(c[i][0] + c[i][3]);
                    float mx = fmaxf(fmaxf(sc[0], sc[1]), fmaxf(sc[2], sc[3]));
                    mx = fmaxf(mx, __shfl_xor_sync(0xffffffffu, mx, 4));
                    mx = fmaxf(mx, __shfl_xor_sync(0xffffffffu, mx, 8));
                    st.m = fmaxf(mx, __shfl_xor_sync(0xffffffffu, mx, 16));
                    uint32_t pv[4];
#pragma unroll
                    for (int i = 0; i < 4; i++) pv[i] = probability(st, sc[i]);
#pragma unroll
                    for (int i = 0; i < 4; i++)
#pragma unroll
                        for (int k = 0; k < 6; k++)
                            mma16816(st.acc[k >> 1], rf[2 * i + 1][k], (g >> 1) == 2 * (k & 1) ? pv[i] : 0u,
                                     (g >> 1) == 2 * (k & 1) + 1 ? pv[i] : 0u);
                }

                uint32_t nrel = (op >> 8) & 3u, ri = 0;
#pragma unroll 1
                for (uint32_t seq = op >> 10; seq > 1u; seq >>= 1) {
                    const bool ring = !(seq & 1u);
                    const bool rel = ring || nrel > 0;
                    uint32_t pv;
                    {
                        const uint32_t s = ring ? rpos : kRing + 2 * ri;
                        wait_tile(s);
                        const uint32_t base = slot0 + s * (8 * kSlotBytes);
                        float c[4] = {};
#pragma unroll
                        for (int k = 0; k < 6; k++) {
                            uint32_t a[4];
                            ldsm4(a, (base + off[k >> 1]) ^ ((k & 1) << 6));
                            const uint2 q = qf[8 * k];
                            mma16816(c, a, q.x, q.y);
                        }
                        if (ring && ++rpos == kRing) rpos = 0;
                        if (rel) release(s);
                        pv = softmax_step(st, c[0] + c[3]);
                    }
                    {
                        const uint32_t s = ring ? rpos : kRing + 2 * ri + 1;
                        wait_tile(s);
                        const uint32_t base = slot0 + s * (8 * kSlotBytes);
#pragma unroll
                        for (int k = 0; k < 6; k++) {
                            uint32_t a[4];
                            ldsm4t(a, (base + off[k >> 1]) ^ ((k & 1) << 6));
                            mma16816(st.acc[k >> 1], a, (g >> 1) == 2 * (k & 1) ? pv : 0u,
                                     (g >> 1) == 2 * (k & 1) + 1 ? pv : 0u);
                        }
                        if (ring && ++rpos == kRing) rpos = 0;
                        if (rel) release(s);
                    }
                    if (!ring) {
                        if (nrel) nrel--;
                        if (++ri == 3) ri = 0;
                    }
                }

                float l = st.l;
                l += __shfl_xor_sync(0xffffffffu, l, 4);
                l += __shfl_xor_sync(0xffffffffu, l, 8);
                l += __shfl_xor_sync(0xffffffffu, l, 16);
                row_acquire();
#pragma unroll
                for (int a = 0; a < 3; a++) {
                    row[64 * a + 16 * t + g] = st.acc[a][0] + st.acc[a][1];
                    row[64 * a + 16 * t + g + 8] = st.acc[a][2] + st.acc[a][3];
                }
                if (lane == 0) { row[192] = st.m; row[193] = l; }
                row_publish();
            } else if (kind == OP_RFLOAD) {
#pragma unroll 1
                for (uint32_t tile = (op >> 2) & 6u; tile <= ((op >> 2) | 1u); tile++) {
                    wait_tile(rpos);
                    const uint32_t base = slot0 + rpos * (8 * kSlotBytes);
#pragma unroll
                    for (int i = 0; i < 8; i++) {
                        if (tile == i) {
#pragma unroll
                            for (int k = 0; k < 6; k++) {
                                if (i & 1) ldsm4t(rf[i][k], (base + off[k >> 1]) ^ ((k & 1) << 6));
                                else ldsm4(rf[i][k], (base + off[k >> 1]) ^ ((k & 1) << 6));
                            }
                        }
                    }
                    ring_release();
                }
            } else if (kind == OP_QPROJ) {
                const uint32_t mask = (op >> 3) & 3u;
#pragma unroll 1
                for (uint32_t b = 0; b < 2; b++)
                    if ((mask >> b) & 1u) mbar_wait(sync0 + kBarXn + 8 * b, (op >> 5) & 1u);
                const uint32_t bb = mask == 3u ? (g & 1) : (mask >> 1);
                const uint32_t* xs = reinterpret_cast<const uint32_t*>(smem + kOffXn) + bb * 80 + 40 * (w >> 2) + 4 * (w & 3) + t;
                float acc[3][4] = {};
#pragma unroll 1
                for (int p = 0; p < 3; p++) {
                    uint32_t xv = xs[p == 2 ? 24 : 16 * p];
                    if (p == 2 && (w & 2) == 0) xv = 0u;
                    wait_tile(rpos);
                    const uint32_t base = sbase + (rpos * 8 + (w & 4)) * kSlotBytes + (w & 3) * 1024 + (lane & 7) * 128 +
                                          (((lane >> 3) ^ (lane & 7)) << 4);
#pragma unroll
                    for (int k = 0; k < 6; k++) {
                        uint32_t a[4];
                        ldsm4t(a, (base ^ ((k & 1) << 6)) + (k >> 1) * 4096);
                        mma16816(acc[k >> 1], a, (g >> 1) == 2 * (k & 1) ? xv : 0u, (g >> 1) == 2 * (k & 1) + 1 ? xv : 0u);
                    }
                    ring_release();
                }
#pragma unroll 1
                for (uint32_t b = 0; b < 2; b++) {
                    if (!((mask >> b) & 1u)) continue;
                    row_acquire();
#pragma unroll
                    for (int a = 0; a < 3; a++) {
                        row[64 * a + 16 * t + g] = b ? acc[a][1] : acc[a][0];
                        row[64 * a + 16 * t + g + 8] = b ? acc[a][3] : acc[a][2];
                    }
                    row_publish();
                }
            } else {
                const uint32_t mask = (op >> 3) & 3u;
#pragma unroll 1
                for (uint32_t b = 0; b < 2; b++)
                    if ((mask >> b) & 1u) mbar_wait(sync0 + kBarO + 8 * b, (op >> 5) & 1u);
                const uint32_t bb = mask == 3u ? (g & 1) : (mask >> 1);
                const uint32_t* ob = reinterpret_cast<const uint32_t*>(smem + kOffObf) + bb * 24 + t;
                const uint32_t roff = ((lane & 7) + 8 * (lane >> 4)) * 160 + ((lane >> 3) & 1) * 16;
                float c[2][4] = {};
#pragma unroll 1
                for (int p = 0; p < 3; p++) {
                    const uint32_t b0 = ob[8 * p], b1 = ob[8 * p + 4];
                    wait_tile(rpos);
                    const uint32_t base = sbase + (rpos * 8 + (w & 4)) * kSlotBytes + (w & 3) * 2560 + roff;
#pragma unroll
                    for (int mt = 0; mt < 5; mt++) {
                        uint32_t a[4];
                        ldsm4t(a, base + mt * 32);
                        const bool on = (g >> 1) == (mt & 3);
                        mma16816(c[mt >> 2], a, on ? b0 : 0u, on ? b1 : 0u);
                    }
                    ring_release();
                }
                row_acquire();
                row[16 * t + g] = c[0][0]; row[80 + 16 * t + g] = c[0][1];
                row[16 * t + g + 8] = c[0][2]; row[80 + 16 * t + g + 8] = c[0][3];
                if (t == 0) {
                    row[64 + g] = c[1][0]; row[144 + g] = c[1][1];
                    row[72 + g] = c[1][2]; row[152 + g] = c[1][3];
                }
                __syncwarp();
#pragma unroll 1
                for (uint32_t b = 0; b < 2; b++)
                    if ((mask >> b) & 1u)
                        st_packet5(&g_y[b][16 * w + (lane >> 1)][cta][lane & 1], row + 80 * b + 5 * (lane >> 1),
                                   1 + ((op >> 5) & 3u));
                __syncwarp();
                if (lane < 2 && ((mask >> lane) & 1u)) mbar_arrive(sync0 + kBarSentY + 8 * lane);
            }
        }
    } else {
        asm volatile("setmaxnreg.dec.sync.aligned.u32 40;");
        if (w == 8) {
            const int rowA = (h * 4096 + 3072 + 256 * jq) * 3, rowB = (h * 4096 + 1024 * jq) * 3;
            const int rowWq = 160 * jq, rowWo = 192 * h + 48 * jq;
            const uint32_t tau = P.tau, tauLow = P.tauLow, tauW = P.tauW, credit = P.credit, winLow = P.winLow, winHigh = P.winHigh;
            const uint64_t polKeep = make_policy(true), polStream = make_policy(false);
            uint32_t fifo = 0, queued = 0, stale = 0, par = 0, nfl = 0, next = now_ns() - credit;
            uint32_t e = P.loads[0];
#pragma unroll 1
            for (uint32_t n = 0; e & LD_VALID; n++) {
                const uint32_t enext = P.loads[n + 1];
                const uint32_t s = (e >> 4) & 15u;
                const uint32_t type = (e >> 1) & 3u;
                const int c1 = ((e >> 10) & 0xfffffu) + ((e & 4u) ? ((e & 2u) ? rowWo : rowWq) : ((e & 2u) ? rowB : rowA));
                const int d1 = (e & 4u) ? ((e & 2u) ? 0 : 80) : 96;
                const uint32_t win = (e & LD_HIT) ? 7u : ((e & LD_LOW) ? winLow : winHigh);
                const uint32_t dt = (e & LD_HIT) ? 0u : ((e & 4u) ? tauW : ((e & LD_LOW) ? tauLow : tau));
                const uint64_t pol = (e & LD_KEEP) ? polKeep : polStream;
#pragma unroll
                for (uint32_t hf = 0; hf < 2; hf++) {
                    for (; nfl >= win; nfl--) {
                        const uint32_t o = (fifo >> (5 * nfl - 5)) & 31u;
                        if ((stale >> o) & 1u) {
                            stale ^= 1u << o;
                        } else {
                            mbar_wait_u(sbase + kOffFull + 8 * o, ((par >> o) & 1u) ^ 1u);
                            queued ^= 1u << o;
                        }
                    }
                    const uint32_t i = 2 * s + hf;
                    if (e & LD_PREFETCH) {
                        if (mbar_test(sbase + kOffEmpty + 16 * s, ((par >> (2 * s)) & 1u) ^ 1u)) break;
                    } else {
                        mbar_wait_u(sbase + kOffEmpty + 8 * i, ((par >> i) & 1u) ^ 1u);
                    }
                    uint32_t now = now_ns();
                    while (dt && (int)(now - next) < 0) now = now_ns();
                    if (elect()) {
                        if (e & LD_PREFETCH) {
                            tma3d_prefetch(&P.tm[e & 7u], 0, c1 + d1 * hf, 0, pol);
                        } else {
                            mbar_expect(sbase + kOffFull + 8 * i, type == 3u ? 10240 : 4 * kSlotBytes);
                            tma3d(sbase + (s * 8 + 4 * hf) * kSlotBytes, &P.tm[e & 7u], 0, c1 + d1 * hf,
                                  type == 2u ? 3 * h : (type == 3u ? 4 * hf : 0), sbase + kOffFull + 8 * i, pol);
                        }
                    }
                    if ((int)(now - credit - next) > 0) next = now - credit;
                    next += dt;
                    if (!(e & LD_PREFETCH)) {
                        stale |= queued & (1u << i);
                        queued &= ~(1u << i);
                        if (!(e & LD_HIT)) {
                            fifo = (fifo << 5) | i;
                            queued |= 1u << i;
                            nfl++;
                        }
                        par ^= 1u << i;
                    }
                }
                e = enext;
            }
        } else {
            if (w == 9) {
#pragma unroll 1
                for (int n = 0;; n++) {
                    const uint32_t job = P.merge[n];
                    if ((job & 3u) == MG_END) break;
                    const uint32_t b = (job >> 2) & 1u;
                    const uint32_t tag = 1 + ((job >> 3) & 3u);
                    mbar_wait(sync0 + kBarRows, n & 1);
                    if ((job & 3u) == MG_Q) {
#pragma unroll 1
                        for (int u = lane; u < 40; u += 32) {
                            float o[5] = {};
#pragma unroll
                            for (int i = 0; i < 8; i++)
#pragma unroll
                                for (int k = 0; k < 5; k++) o[k] += wbuf[i * kWRow + 5 * min(u, 38) + k];
                            st_packet5(&g_q[b][h][jq][u], o, tag);
                        }
                        __syncwarp();
                        if (lane == 0) mbar_arrive(sync0 + kBarSentQ + 8 * b);
                    } else {
                        float* cp = reinterpret_cast<float*>(smem + kOffCpart) + b * kWRow;
                        const bool merge = !(job & 32u);
                        float mi = -INFINITY, li = 0.f;
                        if (lane < 8) { mi = wbuf[lane * kWRow + 192]; li = wbuf[lane * kWRow + 193]; }
                        else if (lane == 8 && merge) { mi = cp[192]; li = cp[193]; }
                        float M = mi;
#pragma unroll
                        for (int o = 8; o > 0; o >>= 1) M = fmaxf(M, __shfl_xor_sync(0xffffffffu, M, o));
                        M = __shfl_sync(0xffffffffu, M, 0);
                        const float sc = ex2((mi - M) * kLog2e);
                        const float L = warp_sum(li * sc);
                        const float ps = __shfl_sync(0xffffffffu, sc, 8);
                        float o[2][3];
#pragma unroll
                        for (int r = 0; r < 2; r++)
#pragma unroll
                            for (int k = 0; k < 3; k++) o[r][k] = merge ? cp[3 * (lane + 32 * r) + k] * ps : 0.f;
#pragma unroll
                        for (int i = 0; i < 8; i++) {
                            const float si = __shfl_sync(0xffffffffu, sc, i);
#pragma unroll
                            for (int r = 0; r < 2; r++)
#pragma unroll
                                for (int k = 0; k < 3; k++)
                                    o[r][k] = fmaf(wbuf[i * kWRow + 3 * (lane + 32 * r) + k], si, o[r][k]);
                        }
                        if (job & 64u) {
#pragma unroll
                            for (int r = 0; r < 2; r++)
                                st_packet(&g_p[b][h][(lane >> 4) + 2 * r][jq][lane & 15], o[r][0], o[r][1], o[r][2], tag);
                            if (lane < 8) st_packet(&g_p[b][h][lane >> 1][jq][16 + (lane & 1)], M, L, 0.f, tag);
                            if (lane == 0) mbar_arrive(sync0 + kBarSentP + 8 * b);
                        } else {
#pragma unroll
                            for (int r = 0; r < 2; r++)
#pragma unroll
                                for (int k = 0; k < 3; k++) cp[3 * (lane + 32 * r) + k] = o[r][k];
                            if (lane == 0) { cp[192] = M; cp[193] = L; }
                        }
                    }
                    __syncwarp();
                    if (lane == 0) mbar_arrive(sync0 + kBarFree);
                }
            } else {
                const uint32_t b = w - 10;
                __nv_bfloat16* const xn = reinterpret_cast<__nv_bfloat16*>(smem + kOffXn) + b * 160;
                __nv_bfloat16* const qd = reinterpret_cast<__nv_bfloat16*>(smem + kOffQf) + b * 192;
                __nv_bfloat16* const ob = reinterpret_cast<__nv_bfloat16*>(smem + kOffObf) + b * 48;
                float xr = lane < 5 ? __bfloat162float(P.x[b * 640 + 5 * cta + lane]) : 0.f;
#pragma unroll 1
                for (uint32_t layer = 0; layer < 4; layer++) {
                    const uint32_t tag = layer + 1;
                    int lane = threadIdx.x & 31;
                    asm volatile("" : "+r"(lane));
                    {
                        uint4 v[4];
                        if (layer == 0) {
#pragma unroll
                            for (int n = 0; n < 4; n++) {
                                const unsigned short* xp = reinterpret_cast<const unsigned short*>(P.x) + b * 640 +
                                                           5 * (lane + 32 * ((jq + n) & 3));
                                v[n].x = xp[0] | ((uint32_t)xp[1] << 16);
                                v[n].y = xp[2] | ((uint32_t)xp[3] << 16);
                                v[n].z = xp[4];
                            }
                        } else {
                            const uint4* src = &g_x[b][lane][0];
                            POLL_UNTIL(
                                v[0] = ld_packet(src + 64 * jq); v[1] = ld_packet(src + 64 * ((jq + 1) & 3));
                                v[2] = ld_packet(src + 64 * (jq ^ 2)); v[3] = ld_packet(src + 64 * ((jq + 3) & 3)),
                                v[0].w == layer && v[1].w == layer && v[2].w == layer && v[3].w == layer);
                        }
                        __syncwarp();
                        TRACE_G(16 + 4 * layer);
                        float sum = 0.f;
#pragma unroll
                        for (int n = 0; n < 4; n++)
                            sum += ((bf_lo(v[n].x) + bf_hi(v[n].x)) + (bf_lo(v[n].y) + bf_hi(v[n].y))) + bf_lo(v[n].z);
                        const float mean = warp_sum(sum) * (1.f / 640.f);
                        float sq = 0.f;
#pragma unroll
                        for (int n = 0; n < 4; n++) {
                            float d;
                            d = bf_lo(v[n].x) - mean; sq = fmaf(d, d, sq);
                            d = bf_hi(v[n].x) - mean; sq = fmaf(d, d, sq);
                            d = bf_lo(v[n].y) - mean; sq = fmaf(d, d, sq);
                            d = bf_hi(v[n].y) - mean; sq = fmaf(d, d, sq);
                            d = bf_lo(v[n].z) - mean; sq = fmaf(d, d, sq);
                        }
                        const float var = warp_sum(sq) * (1.f / 640.f);
                        const float meanb = bf16r(mean);
                        const float den = bf16r(fast_sqrt(bf16r(bf16r(var) + 1e-5f)));
                        xn[5 * lane + 0] = __float2bfloat16_rn(__fdividef(bf16r(bf_lo(v[0].x) - meanb), den));
                        xn[5 * lane + 1] = __float2bfloat16_rn(__fdividef(bf16r(bf_hi(v[0].x) - meanb), den));
                        xn[5 * lane + 2] = __float2bfloat16_rn(__fdividef(bf16r(bf_lo(v[0].y) - meanb), den));
                        xn[5 * lane + 3] = __float2bfloat16_rn(__fdividef(bf16r(bf_hi(v[0].y) - meanb), den));
                        xn[5 * lane + 4] = __float2bfloat16_rn(__fdividef(bf16r(bf_lo(v[0].z) - meanb), den));
                        __syncwarp();
                        if (lane == 0) mbar_arrive(sync0 + kBarXn + 8 * b);
                        TRACE_G(4 * layer);
                    }
                    {
                        mbar_wait(sync0 + kBarSentQ + 8 * b, layer & 1);
                        uint4 v[5];
                        const uint4* src = &g_q[b][h][0][lane];
                        const uint4* ext = &g_q[b][h][lane & 3][lane < 28 ? 32 + (lane >> 2) : 38];
                        POLL_UNTIL(
                            v[0] = ld_packet(src); v[1] = ld_packet(src + 40); v[2] = ld_packet(src + 80);
                            v[3] = ld_packet(src + 120); v[4] = ld_packet(ext),
                            (v[0].w >> 24) == tag && (v[1].w >> 24) == tag && (v[2].w >> 24) == tag &&
                                (v[3].w >> 24) == tag && (v[4].w >> 24) == tag);
                        __syncwarp();
                        TRACE_G(16 + 4 * layer + 1);
                        auto store_q = [&](int d, float q) {
                            qd[(d & ~31) + ((d >> 3) & 1) * 16 + ((d >> 1) & 3) * 4 + ((d >> 4) & 1) * 2 + (d & 1)] =
                                __float2bfloat16_rn(q);
                        };
                        float a[5] = {};
#pragma unroll
                        for (int i = 0; i < 4; i++) add_packet5(a, v[i]);
#pragma unroll
                        for (int k = 0; k < 5; k++) store_q(5 * lane + k, a[k]);
                        float e[5] = {};
                        add_packet5(e, v[4]);
#pragma unroll
                        for (int k = 0; k < 5; k++) {
                            e[k] += __shfl_xor_sync(0xffffffffu, e[k], 1);
                            e[k] += __shfl_xor_sync(0xffffffffu, e[k], 2);
                            const int d = 160 + 5 * (lane >> 2) + k;
                            if ((lane & 3) == 0 && d < 192) store_q(d, e[k]);
                        }
                        __syncwarp();
                        if (lane == 0) mbar_arrive(sync0 + kBarQ + 8 * b);
                        TRACE_G(4 * layer + 1);
                    }
                    if (P.exp) break;
                    {
                        for (uint32_t it = 0; !mbar_try(sync0 + kBarSentP + 8 * b, layer & 1); it++) {
                            if (it > kSpinLimit) __trap();
                            if (layer > 0 && P.keepAlive) {
                                prefetch_l2(&g_y[b][cta][4 * lane][0]);
                                if (lane == (cta >> 2)) prefetch_l2(&g_x[b][cta][0]);
                                prefetch_l2(lane < 20 ? &g_q[b][h][0][8 * lane] : &g_p[b][h][jq][0][8 * min(lane - 20, 8)]);
                            }
                        }
                        uint4 v0, v1, ml;
                        const uint4* src = &g_p[b][h][jq][2 * (lane >> 4)][lane & 15];
                        const uint4* mls = &g_p[b][h][jq][lane & 3][16];
                        POLL_UNTIL(v0 = ld_packet(src); v1 = ld_packet(src + 18); ml = ld_packet(mls),
                                   v0.w == tag && v1.w == tag && ml.w == tag);
                        __syncwarp();
                        TRACE_G(16 + 4 * layer + 2);
                        const float mi = __uint_as_float(ml.x);
                        float M = fmaxf(mi, __shfl_xor_sync(0xffffffffu, mi, 1));
                        M = fmaxf(M, __shfl_xor_sync(0xffffffffu, M, 2));
                        const float sc = ex2((mi - M) * kLog2e);
                        float L = __uint_as_float(ml.y) * sc;
                        L += __shfl_xor_sync(0xffffffffu, L, 1);
                        L += __shfl_xor_sync(0xffffffffu, L, 2);
                        const float s0 = __shfl_sync(0xffffffffu, sc, 2 * (lane >> 4));
                        const float s1 = __shfl_sync(0xffffffffu, sc, 2 * (lane >> 4) + 1);
                        float o0 = fmaf(__uint_as_float(v0.x), s0, __uint_as_float(v1.x) * s1);
                        float o1 = fmaf(__uint_as_float(v0.y), s0, __uint_as_float(v1.y) * s1);
                        float o2 = fmaf(__uint_as_float(v0.z), s0, __uint_as_float(v1.z) * s1);
                        o0 += __shfl_xor_sync(0xffffffffu, o0, 16);
                        o1 += __shfl_xor_sync(0xffffffffu, o1, 16);
                        o2 += __shfl_xor_sync(0xffffffffu, o2, 16);
                        if (lane < 16) {
                            ob[3 * lane] = __float2bfloat16_rn(__fdividef(o0, L));
                            ob[3 * lane + 1] = __float2bfloat16_rn(__fdividef(o1, L));
                            ob[3 * lane + 2] = __float2bfloat16_rn(__fdividef(o2, L));
                        }
                        __syncwarp();
                        if (lane == 0) mbar_arrive(sync0 + kBarO + 8 * b);
                        TRACE_G(4 * layer + 2);
                    }
                    {
                        mbar_wait(sync0 + kBarSentY + 8 * b, layer & 1);
                        uint4 v[4];
                        const uint4* src = &g_y[b][cta][lane][0];
                        POLL_UNTIL(
                            v[0] = ld_packet(src); v[1] = ld_packet(src + 64); v[2] = ld_packet(src + 128);
                            v[3] = ld_packet(src + 192),
                            (v[0].w >> 24) == tag && (v[1].w >> 24) == tag && (v[2].w >> 24) == tag && (v[3].w >> 24) == tag);
                        __syncwarp();
                        TRACE_G(16 + 4 * layer + 3);
                        float a[5] = {};
#pragma unroll
                        for (int i = 0; i < 4; i++) add_packet5(a, v[i]);
#pragma unroll
                        for (int k = 0; k < 5; k++) a[k] = warp_sum(a[k]);
                        const float y = lane == 0 ? a[0] : lane == 1 ? a[1] : lane == 2 ? a[2] : lane == 3 ? a[3] : a[4];
                        xr = bf16r(xr + bf16r(y));
                        if (layer == 3) {
                            if (lane < 5) P.out[b * 640 + 5 * cta + lane] = __float2bfloat16_rn(xr);
                        } else {
                            const uint32_t pr = pack_bf16(xr, __shfl_down_sync(0xffffffffu, xr, 1));
                            const uint32_t p01 = __shfl_sync(0xffffffffu, pr, 0);
                            const uint32_t p23 = __shfl_sync(0xffffffffu, pr, 2);
                            const uint32_t p4 = __shfl_sync(0xffffffffu, pr, 4);
                            if (lane < 2) st_packet(&g_x[b][cta][lane], p01, p23, p4, tag);
                        }
                        TRACE_G(4 * layer + 3);
                    }
                }
            }
        }
    }
}

struct Sched {
    Params& P;
    int np = 0, nm = 0, nl = 0, rslot = 0, mark = 0;
    void low_begin(int back) { mark = nl - back; }
    void low_end(int back) { for (int i = mark; i < nl - back; i++) P.loads[i] |= LD_LOW; }
    enum { RF = 1 << 7, RETA = 1 << 8, RETB = 1 << 9, FIRST = 1 << 11, PUB = 1 << 12 };
    void ring(uint32_t e) {
        P.loads[nl++] = e | (rslot << 4);
        rslot = (rslot + 1) % kRing;
    }
    static uint32_t tile(int isB, int b, int idx, int v) {
        return LD_VALID | (2 * isB + v) | (uint32_t)((b * 32 * 4096 + 64 * idx) * 3) << 10;
    }
    void kv(int isB, int b, int idx, uint32_t fk = 0, uint32_t fv = 0) {
        ring(tile(isB, b, idx, 0) | fk);
        ring(tile(isB, b, idx, 1) | fv);
    }
    void ret(int b, int base, int i) { P.loads[nl++] = tile(1, b, base + i / 2, i & 1) | ((kRing + i) << 4); }
    void qproj(int mask, int layer) {
        for (int p = 0; p < 3; p++) ring(LD_VALID | (4 + (layer & 1)) | (p == 2 ? 48 : 32 * p) << 10);
        P.prog[np++] = OP_QPROJ | (mask << 3) | (layer << 5);
        for (int b = 0; b < 2; b++)
            if ((mask >> b) & 1) P.merge[nm++] = MG_Q | (b << 2) | (layer << 3);
    }
    void oproj(int mask, int layer) {
        for (int p = 0; p < 3; p++) ring(LD_VALID | (6 + (layer & 1)) | (16 * p) << 10);
        P.prog[np++] = OP_OPROJ | (mask << 3) | (layer << 5);
    }
    void rfload(int pair, int isB, int b, int idx) {
        kv(isB, b, idx);
        P.prog[np++] = OP_RFLOAD | (pair << 3);
    }
    void seg(int b, int layer, uint32_t flags, int nring, int retPos = 0, int retStep = 1) {
        uint32_t seq = 0;
        int n = 0, left = (flags & RETB) ? 3 : 0;
        for (int i = 0; i <= nring; i++) {
            if ((flags & RETA) && i < 3) seq |= 1u << n++;
            while (left > 0 && (i == nring || i == retPos + (3 - left) * retStep)) { seq |= 1u << n++; left--; }
            if (i < nring) n++;
        }
        seq |= 1u << n;
        P.prog[np++] = OP_SEG | (b << 3) | ((layer & 1) << 4) | (flags & RF) | ((flags & RETA) ? 3u << 8 : 0) | (seq << 10);
        P.merge[nm++] = MG_ATTN | (b << 2) | (layer << 3) | ((flags & FIRST) ? 32 : 0) | ((flags & PUB) ? 64 : 0);
    }
};

int tune(const char* name, int dflt) {
    (void)name;
    return dflt;
}

void build_schedule(Params& P) {
    for (int i = 0; i < kMaxProg; i++) P.prog[i] = P.merge[i] = 0;
    for (int i = 0; i < kMaxLoads; i++) P.loads[i] = LD_NONE;
    P.winLow = tune("WINLOW", 4);
    P.winHigh = tune("WINHIGH", 6);
    P.tau = tune("TAU", 490);
    P.tauLow = tune("TAULOW", P.tau);
    P.tauW = tune("TAUW", P.tauLow * 5 / 6);
    P.credit = tune("CREDIT", 1000);
    P.keepAlive = tune("KEEPALIVE", 0);
    Sched S{P};
    using F = Sched;
    const int keep[2] = {tune("KEEP0", 8), tune("KEEP1", 8)};
    auto kept = [&](int b, int idx, int v) { return (2 * (15 - idx) + (1 - v)) < keep[b]; };
    const int hit0 = 16 - (keep[0] + 1) / 2, hit1 = 16 - (keep[1] + 1) / 2;
    int next0 = 3, next1 = 7;
    auto fill0 = [&](int n, uint32_t flags = 0) {
        int c = 0;
        for (; c < n && next0 < hit0; c++) S.kv(1, 0, next0++);
        if (c > 0 || flags) S.seg(0, 3, flags, c);
    };
    auto fill1 = [&](int n) {
        int c = 0;
        const uint32_t flags = next1 == 7 ? F::FIRST : 0;
        for (; c < n && next1 < hit1; c++) S.kv(1, 1, next1++);
        if (c > 0) S.seg(1, 1, flags, c);
    };
    auto second_pass = [&](int b, int idx0, int rb, int rbase) {
        int r = 0, n = 0;
        for (int i = idx0; i < 16; i++)
            for (int v = 0; v < 2; v++) {
                if (n >= kRing && (n & 1) && r < 6) { S.ret(rb, rbase, r++); S.ret(rb, rbase, r++); }
                n++;
                S.ring(F::tile(1, b, i, v) | (kept(b, i, v) && tune("HITFLAG", 1) ? LD_HIT : 0));
            }
        while (r < 6) S.ret(rb, rbase, r++);
    };

    P.exp = tune("EXP", 0);
    if (P.exp) {
        S.qproj(3, 0);
        const int k = tune("EXPKEEP", 0);
        for (int r = 0; r < 2; r++)
            for (int b = 0; b < 2; b++) {
                for (int i = 0; i < 15; i++) S.kv(1, b, i, (i >= 15 - k) ? LD_KEEP : 0, (i >= 15 - k) ? LD_KEEP : 0);
                S.seg(b, 0, F::FIRST, 15);
            }
        return;
    }
    S.qproj(3, 0);
    for (int i = 0; i < 4; i++) S.rfload(i, 0, 0, i);
    S.seg(0, 0, F::RF | F::FIRST | F::PUB, 0);
    for (int i = 0; i < 4; i++) S.kv(0, 1, i);
    S.seg(1, 0, F::FIRST | F::PUB, 4);
    const int lb = tune("LOWBACK", 0);
    S.low_begin(lb);
    S.oproj(3, 0);
    for (int i = 0; i < 6; i++) S.ret(0, 0, i);
    S.qproj(3, 1);
    const int npf = tune("NPF", 4);
    for (int n = 0; n < npf; n++) P.loads[S.nl++] = F::tile(1, 0, 15 - n / 2, 1 - (n & 1)) | LD_KEEP | LD_PREFETCH | (S.rslot << 4);
    for (int i = 3; i < 16; i++) {
        const int pfhit = tune("PFHIT", npf);
        S.kv(1, 0, i, (kept(0, i, 0) ? LD_KEEP : 0) | (2 * (15 - i) + 1 < pfhit ? LD_HIT : 0),
             (kept(0, i, 1) ? LD_KEEP : 0) | (2 * (15 - i) < pfhit ? LD_HIT : 0));
        if (i == 4) S.low_end(1);
    }
    S.seg(0, 1, F::RETB | F::FIRST | F::PUB, 13, tune("RP1", 3), tune("RS1", 3));
    S.low_begin(lb);
    fill1(tune("F21", 1));
    S.oproj(1, 1);
    fill1(tune("F22", 2));
    S.qproj(1, 2);
    fill1(16);
    S.seg(0, 2, F::RF | F::FIRST | F::PUB, 0);
    S.rfload(0, 1, 1, 3);
    S.oproj(1, 2);
    S.rfload(1, 1, 1, 4);
    S.rfload(2, 1, 1, 5);
    S.qproj(1, 3);
    S.rfload(3, 1, 1, 6);
    S.low_end(0);
    second_pass(0, hit0, 1, 0);
    S.seg(0, 3, F::RETA | F::FIRST, 16 - hit0);
    for (int i = hit1; i < 16; i++) S.kv(1, 1, i, kept(1, i, 0) ? LD_KEEP : 0, kept(1, i, 1) ? LD_KEEP : 0);
    S.seg(1, 1, F::RF | F::RETB | F::PUB, 16 - hit1, tune("RP2", 2), tune("RS2", 1));
    S.low_begin(lb);
    fill0(tune("F41", 1));
    S.oproj(2, 1);
    fill0(tune("F42", 2));
    S.qproj(2, 2);
    fill0(tune("F43", 1));
    for (int i = 0; i < 4; i++) S.kv(0, 1, i);
    S.seg(1, 2, F::FIRST | F::PUB, 4);
    fill0(tune("F51", 1));
    S.oproj(2, 2);
    fill0(tune("F52", 2));
    S.qproj(2, 3);
    fill0(16, F::PUB);
    S.low_end(0);
    second_pass(1, 10, 1, 7);
    S.seg(1, 3, F::RF | F::RETA | F::RETB | F::FIRST | F::PUB, 6, tune("RP3", 6), tune("RS3", 1));
    S.oproj(3, 3);
}

typedef CUresult (*EncodeFn)(CUtensorMap*, CUtensorMapDataType, cuuint32_t, void*, const cuuint64_t*,
                             const cuuint64_t*, const cuuint32_t*, const cuuint32_t*, CUtensorMapInterleave,
                             CUtensorMapSwizzle, CUtensorMapL2promotion, CUtensorMapFloatOOBfill);

}

extern "C" void kernel_launch(void* const* d_in, const int* in_sizes, int n_in, void* d_out, int out_size) {
    (void)in_sizes; (void)n_in; (void)out_size;
    Params P;
    void* fn = nullptr;
    cudaDriverEntryPointQueryResult qr;
    cudaGetDriverEntryPoint("cuTensorMapEncodeTiled", &fn, cudaEnableDefault, &qr);
    EncodeFn encode = reinterpret_cast<EncodeFn>(fn);
    const CUtensorMapL2promotion promo = (CUtensorMapL2promotion)tune("PROMO", CU_TENSOR_MAP_L2_PROMOTION_NONE);
    void* kv[4] = {d_in[1], d_in[2], d_in[6], d_in[7]};
    for (int i = 0; i < 4; i++) {
        const cuuint64_t dims[3] = {64, 2ull * 32 * 4096 * 3, 1};
        const cuuint64_t strides[2] = {128, 2ull * 32 * 4096 * 3 * 128};
        const cuuint32_t box[3] = {64, 96, 1};
        const cuuint32_t es[3] = {1, 1, 1};
        encode(&P.tm[i], CU_TENSOR_MAP_DATA_TYPE_BFLOAT16, 3, kv[i], dims, strides, box, es,
               CU_TENSOR_MAP_INTERLEAVE_NONE, CU_TENSOR_MAP_SWIZZLE_128B, promo, CU_TENSOR_MAP_FLOAT_OOB_FILL_NONE);
    }
    void* wq[2] = {d_in[3], d_in[8]};
    for (int i = 0; i < 2; i++) {
        const cuuint64_t dims[3] = {64, 640, 96};
        const cuuint64_t strides[2] = {12288, 128};
        const cuuint32_t box[3] = {64, 32, 3};
        const cuuint32_t es[3] = {1, 1, 1};
        encode(&P.tm[4 + i], CU_TENSOR_MAP_DATA_TYPE_BFLOAT16, 3, wq[i], dims, strides, box, es,
               CU_TENSOR_MAP_INTERLEAVE_NONE, CU_TENSOR_MAP_SWIZZLE_128B, promo, CU_TENSOR_MAP_FLOAT_OOB_FILL_NONE);
    }
    void* wo[2] = {d_in[4], d_in[9]};
    for (int i = 0; i < 2; i++) {
        const cuuint64_t dims[3] = {80, 6144, 8};
        const cuuint64_t strides[2] = {1280, 160};
        const cuuint32_t box[3] = {80, 16, 4};
        const cuuint32_t es[3] = {1, 1, 1};
        encode(&P.tm[6 + i], CU_TENSOR_MAP_DATA_TYPE_BFLOAT16, 3, wo[i], dims, strides, box, es,
               CU_TENSOR_MAP_INTERLEAVE_NONE, CU_TENSOR_MAP_SWIZZLE_NONE, promo, CU_TENSOR_MAP_FLOAT_OOB_FILL_NONE);
    }
    P.x = static_cast<const __nv_bfloat16*>(d_in[0]);
    P.out = static_cast<__nv_bfloat16*>(d_out);
    build_schedule(P);
    cudaFuncSetAttribute(fused_decode_kernel, cudaFuncAttributeMaxDynamicSharedMemorySize, kSmemBytes);
    fused_decode_kernel<<<kCtas, kThreads, kSmemBytes>>>(P);
}
```

```cpp
#include <cuda_runtime.h>
#include <cuda_bf16.h>
#include <cuda.h>
#include <stdint.h>

namespace {

constexpr int kCtas = 128;
constexpr int kThreads = 384;
constexpr int kSlotBytes = 3072;
constexpr int kRing = 3;
constexpr int kSlots = 9;
constexpr int kWRow = 196;

constexpr int kOffWbuf = kSlots * 8 * kSlotBytes;
constexpr int kOffCpart = kOffWbuf + 8 * kWRow * 4;
constexpr int kOffQf = kOffCpart + 2 * kWRow * 4;
constexpr int kOffXn = kOffQf + 2 * 96 * 4;
constexpr int kOffObf = kOffXn + 2 * 160 * 2;
constexpr int kOffFull = kOffObf + 2 * 48 * 2;
constexpr int kOffEmpty = kOffFull + kSlots * 8;
constexpr int kOffSync = kOffEmpty + kSlots * 8;
constexpr int kOffAnchor = kOffSync + 14 * 8;
constexpr int kSmemBytes = kOffAnchor + 8;
static_assert(kSmemBytes <= 232448, "shared memory budget");
constexpr int kBarRows = 0, kBarFree = 8, kBarQ = 16, kBarXn = 32, kBarO = 48;
constexpr int kBarSentQ = 64, kBarSentP = 80, kBarSentY = 96;

constexpr int kMaxProg = 48;
constexpr int kMaxLoads = 200;

enum : uint32_t { OP_END = 0, OP_QPROJ = 1, OP_RFLOAD = 2, OP_SEG = 3, OP_OPROJ = 4 };
enum : uint32_t { LD_NONE = 0, LD_KEEP = 1u << 3, LD_LOW = 1u << 8, LD_VALID = 1u << 9, LD_ANCHOR = 1u << 29, LD_HIT = 1u << 31 };
enum : uint32_t { MG_END = 0, MG_ATTN = 1, MG_Q = 2 };

struct alignas(64) Params {
    CUtensorMap tm[8];
    const __nv_bfloat16* x;
    __nv_bfloat16* out;
    uint32_t winLow, winHigh;
    uint32_t tau, tauLow, tauW, credit;
    uint32_t look, lookDelay, lookBack;
    uint32_t anchorDelay, credit0;
    uint32_t exp;
    uint32_t prog[kMaxProg];
    uint32_t merge[kMaxProg];
    uint32_t loads[kMaxLoads];
};

__device__ uint4 g_q[2][32][4][40];
__device__ uint4 g_p[2][32][4][4][18];
constexpr int kAccPackets = 216;
constexpr float kAccDone = 129.f;
__device__ float4 g_acc[2][3][kAccPackets];
constexpr int kOutReplicas = 8;
__device__ float4 g_out[2][kOutReplicas][kAccPackets];

#define SPINNS 30
#define SLEEPNS 200
#define POLL_SLEEP __nanosleep(SLEEPNS)
constexpr uint32_t kSpinLimit = 1u << 22;

__device__ __forceinline__ void mbar_init(uint32_t bar, uint32_t count) {
    asm volatile("mbarrier.init.shared::cta.b64 [%0], %1;" ::"r"(bar), "r"(count) : "memory");
}
__device__ __forceinline__ void mbar_arrive(uint32_t bar) {
    asm volatile("mbarrier.arrive.shared::cta.b64 _, [%0];" ::"r"(bar) : "memory");
}
__device__ __forceinline__ bool mbar_test(uint32_t bar, uint32_t parity) {
    uint32_t ok;
    asm volatile(
        "{\n\t.reg .pred p;\n\t"
        "mbarrier.test_wait.parity.shared::cta.b64 p, [%1], %2;\n\t"
        "selp.u32 %0, 1, 0, p;\n\t}"
        : "=r"(ok) : "r"(bar), "r"(parity) : "memory");
    return __all_sync(0xffffffffu, ok);
}
__device__ __forceinline__ void mbar_expect(uint32_t bar, uint32_t bytes) {
    asm volatile("mbarrier.arrive.expect_tx.shared::cta.b64 _, [%0], %1;" ::"r"(bar), "r"(bytes) : "memory");
}
__device__ __forceinline__ void mbar_wait(uint32_t bar, uint32_t parity) {
    uint32_t ok, it = 0;
    do {
        asm volatile(
            "{\n\t.reg .pred p;\n\t"
            "mbarrier.try_wait.parity.shared::cta.b64 p, [%1], %2;\n\t"
            "selp.u32 %0, 1, 0, p;\n\t}"
            : "=r"(ok) : "r"(bar), "r"(parity) : "memory");
        if (++it > kSpinLimit) __trap();
    } while (!ok);
}
__device__ __forceinline__ bool mbar_try(uint32_t bar, uint32_t parity) {
    uint32_t ok;
    asm volatile(
        "{\n\t.reg .pred p;\n\t"
        "mbarrier.try_wait.parity.shared::cta.b64 p, [%1], %2;\n\t"
        "selp.u32 %0, 1, 0, p;\n\t}"
        : "=r"(ok) : "r"(bar), "r"(parity) : "memory");
    return __all_sync(0xffffffffu, ok);
}
__device__ __forceinline__ void mbar_wait_u(uint32_t bar, uint32_t parity) {
    for (uint32_t it = 0; !mbar_try(bar, parity); it++)
        if (it > kSpinLimit) __trap();
}
__device__ __forceinline__ void prefetch_l2(const void* p) {
    asm volatile("prefetch.global.L2 [%0];" ::"l"(p) : "memory");
}
__device__ __forceinline__ void tma3d(uint32_t dst, const CUtensorMap* tm, int c0, int c1, int c2, uint32_t bar, uint64_t pol) {
    asm volatile(
        "cp.async.bulk.tensor.3d.shared::cluster.global.mbarrier::complete_tx::bytes.L2::cache_hint "
        "[%0], [%1, {%2, %3, %4}], [%5], %6;"
        ::"r"(dst), "l"(tm), "r"(c0), "r"(c1), "r"(c2), "r"(bar), "l"(pol) : "memory");
}
__device__ __forceinline__ void tma3d_prefetch(const CUtensorMap* tm, int c0, int c1, int c2, uint64_t pol) {
    asm volatile("cp.async.bulk.prefetch.tensor.3d.L2.global.L2::cache_hint [%0, {%1, %2, %3}], %4;"
                 ::"l"(tm), "r"(c0), "r"(c1), "r"(c2), "l"(pol) : "memory");
}
__device__ __forceinline__ uint64_t make_policy(bool keep) {
    uint64_t pol;
    if (keep) asm volatile("createpolicy.fractional.L2::evict_normal.b64 %0, 1.0;" : "=l"(pol));
    else      asm volatile("createpolicy.fractional.L2::evict_first.b64 %0, 1.0;" : "=l"(pol));
    return pol;
}
__device__ __forceinline__ void ldsm4(uint32_t (&r)[4], uint32_t addr) {
    asm volatile("ldmatrix.sync.aligned.m8n8.x4.shared.b16 {%0,%1,%2,%3}, [%4];"
                 : "=r"(r[0]), "=r"(r[1]), "=r"(r[2]), "=r"(r[3]) : "r"(addr) : "memory");
}
__device__ __forceinline__ void ldsm4t(uint32_t (&r)[4], uint32_t addr) {
    asm volatile("ldmatrix.sync.aligned.m8n8.x4.trans.shared.b16 {%0,%1,%2,%3}, [%4];"
                 : "=r"(r[0]), "=r"(r[1]), "=r"(r[2]), "=r"(r[3]) : "r"(addr) : "memory");
}
__device__ __forceinline__ void mma16816(float (&c)[4], const uint32_t (&a)[4], uint32_t b0, uint32_t b1) {
    asm volatile("mma.sync.aligned.m16n8k16.row.col.f32.bf16.bf16.f32 {%0,%1,%2,%3}, {%4,%5,%6,%7}, {%8,%9}, {%0,%1,%2,%3};"
                 : "+f"(c[0]), "+f"(c[1]), "+f"(c[2]), "+f"(c[3])
                 : "r"(a[0]), "r"(a[1]), "r"(a[2]), "r"(a[3]), "r"(b0), "r"(b1));
}
__device__ __forceinline__ float bf16r(float v) { return __bfloat162float(__float2bfloat16_rn(v)); }
__device__ __forceinline__ uint32_t pack_bf16(float lo, float hi) {
    uint32_t r;
    asm("cvt.rn.bf16x2.f32 %0, %1, %2;" : "=r"(r) : "f"(hi), "f"(lo));
    return r;
}
__device__ __forceinline__ bool elect() {
    uint32_t p;
    asm volatile("{\n\t.reg .pred e;\n\telect.sync _|e, 0xffffffff;\n\tselp.u32 %0, 1, 0, e;\n\t}" : "=r"(p));
    return p;
}
__device__ __forceinline__ float fast_sqrt(float v) {
    float r;
    asm("sqrt.approx.f32 %0, %1;" : "=f"(r) : "f"(v));
    return r;
}
__device__ __forceinline__ float ex2(float v) {
    float r;
    asm("ex2.approx.ftz.f32 %0, %1;" : "=f"(r) : "f"(v));
    return r;
}
__device__ __forceinline__ void st_packet(uint4* p, uint32_t a, uint32_t b, uint32_t c, uint32_t tag) {
    asm volatile(
        "{\n\t.reg .b64 lo, hi;\n\t.reg .b128 v;\n\t"
        "mov.b64 lo, {%1, %2};\n\tmov.b64 hi, {%3, %4};\n\tmov.b128 v, {lo, hi};\n\t"
        "st.relaxed.gpu.global.b128 [%0], v;\n\t}"
        ::"l"(p), "r"(a), "r"(b), "r"(c), "r"(tag) : "memory");
}
__device__ __forceinline__ void st_packet(uint4* p, float a, float b, float c, uint32_t tag) {
    st_packet(p, __float_as_uint(a), __float_as_uint(b), __float_as_uint(c), tag);
}
__device__ __forceinline__ uint4 ld_packet(const uint4* p) {
    uint4 v;
    asm volatile(
        "{\n\t.reg .b64 lo, hi;\n\t.reg .b128 v;\n\t"
        "ld.relaxed.gpu.global.b128 v, [%4];\n\t"
        "mov.b128 {lo, hi}, v;\n\tmov.b64 {%0, %1}, lo;\n\tmov.b64 {%2, %3}, hi;\n\t}"
        : "=r"(v.x), "=r"(v.y), "=r"(v.z), "=r"(v.w) : "l"(p) : "memory");
    return v;
}
__device__ __forceinline__ void red_packet(float4* p, float a, float b, float c) {
    asm volatile("red.relaxed.gpu.global.add.v4.f32 [%0], {%1, %2, %3, %4};"
                 ::"l"(p), "f"(a), "f"(b), "f"(c), "f"(1.f) : "memory");
}
#define POLL_UNTIL(loads, done)                 \
    for (uint32_t it_ = 0;; it_++) {            \
        loads;                                  \
        if (__all_sync(0xffffffffu, done)) break; \
        if (it_ > kSpinLimit) __trap();         \
        POLL_SLEEP;                             \
    }
__device__ __forceinline__ uint32_t round24(float v) {
    const uint32_t u = __float_as_uint(v);
    return u + ((u & 0x7f800000u) == 0x7f800000u ? 0u : 0x80u);
}
__device__ __forceinline__ void st_packet5(uint4* p, const float* v, uint32_t tag) {
    const uint32_t r0 = round24(v[0]), r1 = round24(v[1]), r2 = round24(v[2]), r3 = round24(v[3]), r4 = round24(v[4]);
    st_packet(p, __byte_perm(r0, r1, 0x5321), __byte_perm(r1, r2, 0x6532), __byte_perm(r2, r3, 0x7653),
              (r4 >> 8) | (tag << 24));
}
__device__ __forceinline__ void add_packet5(float (&a)[5], const uint4& v) {
    a[0] += __uint_as_float(v.x << 8);
    a[1] += __uint_as_float(__funnelshift_r(v.x, v.y, 16) & 0xffffff00u);
    a[2] += __uint_as_float(__funnelshift_r(v.y, v.z, 8) & 0xffffff00u);
    a[3] += __uint_as_float(v.z & 0xffffff00u);
    a[4] += __uint_as_float(v.w << 8);
}
__device__ __forceinline__ uint32_t now_ns() {
    uint32_t t;
    asm volatile("mov.u32 %0, %globaltimer_lo;" : "=r"(t));
    return t;
}
__device__ __forceinline__ float bf_lo(uint32_t v) { return __uint_as_float(v << 16); }
__device__ __forceinline__ float bf_hi(uint32_t v) { return __uint_as_float(v & 0xffff0000u); }
__device__ __forceinline__ float warp_sum(float v) {
#pragma unroll
    for (int o = 16; o > 0; o >>= 1) v += __shfl_xor_sync(0xffffffffu, v, o);
    return v;
}

constexpr float kLog2e = 1.4426950408889634f;
constexpr float kScale = 0.07216878364870322f;

struct Attn {
    float m, l;
    float acc[3][4];
};

__device__ __forceinline__ float score(float dot) { return bf16r(bf16r(dot) * kScale); }

__device__ __forceinline__ uint32_t probability(Attn& st, float s) {
    const float e = ex2((s - st.m) * kLog2e);
    st.l += e;
    const float hi = bf16r(e);
    const uint32_t hl = pack_bf16(hi, e - hi);
    uint32_t pv;
    asm volatile("movmatrix.sync.aligned.m8n8.trans.b16 %0, %1;" : "=r"(pv) : "r"(hl));
    return pv;
}

__device__ __forceinline__ uint32_t softmax_step(Attn& st, float dot) {
    const float s = score(dot);
    if (__any_sync(0xffffffffu, s > st.m)) {
        float mx = fmaxf(s, __shfl_xor_sync(0xffffffffu, s, 4));
        mx = fmaxf(mx, __shfl_xor_sync(0xffffffffu, mx, 8));
        mx = fmaxf(mx, __shfl_xor_sync(0xffffffffu, mx, 16));
        mx = fmaxf(mx, st.m);
        const float corr = ex2((st.m - mx) * kLog2e);
        st.m = mx;
        st.l *= corr;
#pragma unroll
        for (int a = 0; a < 3; a++)
#pragma unroll
            for (int i = 0; i < 4; i++) st.acc[a][i] *= corr;
    }
    return probability(st, s);
}

#define TRACE_G(i)
#define TRACE_C(i)

__global__ void __launch_bounds__(kThreads, 1)
fused_decode_kernel(const __grid_constant__ Params P) {
    extern __shared__ __align__(1024) unsigned char smem[];
    const uint32_t sbase = (uint32_t)__cvta_generic_to_shared(smem);
    const uint32_t sync0 = sbase + kOffSync;
    float* const wbuf = reinterpret_cast<float*>(smem + kOffWbuf);

    const int lane = threadIdx.x & 31;
    const int w = __shfl_sync(0xffffffffu, threadIdx.x >> 5, 0);
    const int cta = blockIdx.x;
    const int h = cta >> 2, jq = cta & 3;

    if (elect()) {
        if (w == 8) {
#pragma unroll
            for (int i = 0; i < kSlots; i++) {
                mbar_init(sbase + kOffFull + 8 * i, 1);
                mbar_init(sbase + kOffEmpty + 8 * i, 8);
            }
        } else if (w == 9) {
#pragma unroll
            for (int i = 0; i < 8; i++) asm volatile("prefetch.tensormap [%0];" ::"l"(&P.tm[i]) : "memory");
        } else if (w == 10) {
#pragma unroll
            for (int i = 0; i < 14; i++) mbar_init(sync0 + 8 * i, (8 * i == kBarRows || 8 * i >= kBarSentY) ? 8 : 1);
        }
        if (w != 9) asm volatile("fence.mbarrier_init.release.cluster;" ::: "memory");
    }
    __syncwarp();
    if (w == 8) asm volatile("bar.arrive 1, %0;" ::"n"(kThreads) : "memory");
    else asm volatile("bar.sync 1, %0;" ::"n"(kThreads) : "memory");

    if (w < 8) {
        asm volatile("setmaxnreg.inc.sync.aligned.u32 232;");
        const uint32_t slot0 = sbase + w * kSlotBytes;
        const uint32_t full0 = sbase + kOffFull;

        uint32_t off[3];
#pragma unroll
        for (int u = 0; u < 3; u++) {
            const int line = 3 * (lane & 7) + u;
            off[u] = line * 128 + (((lane >> 3) ^ (line & 7)) << 4);
        }
        uint32_t par = 0, rpos = 0, nrows = 0;
        auto wait_tile = [&](uint32_t s) { mbar_wait(full0 + 8 * s, (par >> s) & 1u); };
        auto release = [&](uint32_t s) {
            par ^= 1u << s;
            __syncwarp();
            if (elect()) mbar_arrive(full0 + 8 * s + (kOffEmpty - kOffFull));
        };
        auto ring_release = [&]() {
            release(rpos);
            if (++rpos == kRing) rpos = 0;
        };
        auto row_acquire = [&]() { mbar_wait(sync0 + kBarFree, (nrows & 1) ^ 1); };
        auto row_publish = [&]() {
            __syncwarp();
            if (elect()) mbar_arrive(sync0 + kBarRows);
            nrows++;
        };

        uint32_t rf[8][6][4];
#pragma unroll
        for (int i = 0; i < 8; i++)
#pragma unroll
            for (int s = 0; s < 6; s++)
#pragma unroll
                for (int k = 0; k < 4; k++) rf[i][s][k] = 0;

#pragma unroll 1
        for (int pc = 0;; pc++) {
            const uint32_t op = P.prog[pc];
            const uint32_t kind = op & 7u;
            if (kind == OP_END) break;
            int lane = threadIdx.x & 31;
            asm volatile("" : "+r"(lane));
            const int g = lane >> 2, t = lane & 3;
            float* const row = wbuf + w * kWRow;

            if (kind == OP_SEG) {
                const uint32_t b = (op >> 3) & 1u;
                mbar_wait(sync0 + kBarQ + 8 * b, (op >> 4) & 1u);
                const uint2* qf = reinterpret_cast<const uint2*>(smem + kOffQf) + b * 48 + (lane & 7);
                Attn st;
                st.m = -INFINITY; st.l = 0.f;
#pragma unroll
                for (int a = 0; a < 3; a++)
#pragma unroll
                    for (int i = 0; i < 4; i++) st.acc[a][i] = 0.f;

                if (op & (1u << 7)) {
                    float c[4][4] = {};
#pragma unroll
                    for (int k = 0; k < 6; k++) {
                        const uint2 q = qf[8 * k];
#pragma unroll
                        for (int i = 0; i < 4; i++) mma16816(c[i], rf[2 * i][k], q.x, q.y);
                    }
                    float sc[4];
#pragma unroll
                    for (int i = 0; i < 4; i++) sc[i] = score(c[i][0] + c[i][3]);
                    float mx = fmaxf(fmaxf(sc[0], sc[1]), fmaxf(sc[2], sc[3]));
                    mx = fmaxf(mx, __shfl_xor_sync(0xffffffffu, mx, 4));
                    mx = fmaxf(mx, __shfl_xor_sync(0xffffffffu, mx, 8));
                    st.m = fmaxf(mx, __shfl_xor_sync(0xffffffffu, mx, 16));
                    uint32_t pv[4];
#pragma unroll
                    for (int i = 0; i < 4; i++) pv[i] = probability(st, sc[i]);
#pragma unroll
                    for (int i = 0; i < 4; i++)
#pragma unroll
                        for (int k = 0; k < 6; k++)
                            mma16816(st.acc[k >> 1], rf[2 * i + 1][k], (g >> 1) == 2 * (k & 1) ? pv[i] : 0u,
                                     (g >> 1) == 2 * (k & 1) + 1 ? pv[i] : 0u);
                }

                uint32_t nrel = (op >> 8) & 3u, ri = 0;
#pragma unroll 1
                for (uint32_t seq = op >> 10; seq > 1u; seq >>= 1) {
                    const bool ring = !(seq & 1u);
                    const bool rel = ring || nrel > 0;
                    uint32_t pv;
                    {
                        const uint32_t s = ring ? rpos : kRing + 2 * ri;
                        wait_tile(s);
                        TRACE_C(5);
                        const uint32_t base = slot0 + s * (8 * kSlotBytes);
                        float c[4] = {};
#pragma unroll
                        for (int k = 0; k < 6; k++) {
                            uint32_t a[4];
                            ldsm4(a, (base + off[k >> 1]) ^ ((k & 1) << 6));
                            const uint2 q = qf[8 * k];
                            mma16816(c, a, q.x, q.y);
                        }
                        if (ring && ++rpos == kRing) rpos = 0;
                        if (rel) release(s);
                        TRACE_C(6);
                        pv = softmax_step(st, c[0] + c[3]);
                        TRACE_C(7);
                    }
                    {
                        const uint32_t s = ring ? rpos : kRing + 2 * ri + 1;
                        wait_tile(s);
                        TRACE_C(8);
                        const uint32_t base = slot0 + s * (8 * kSlotBytes);
#pragma unroll
                        for (int k = 0; k < 6; k++) {
                            uint32_t a[4];
                            ldsm4t(a, (base + off[k >> 1]) ^ ((k & 1) << 6));
                            mma16816(st.acc[k >> 1], a, (g >> 1) == 2 * (k & 1) ? pv : 0u,
                                     (g >> 1) == 2 * (k & 1) + 1 ? pv : 0u);
                        }
                        if (ring && ++rpos == kRing) rpos = 0;
                        if (rel) release(s);
                    }
                    if (!ring) {
                        if (nrel) nrel--;
                        if (++ri == 3) ri = 0;
                    }
                }

                TRACE_C(4);
                float l = st.l;
                l += __shfl_xor_sync(0xffffffffu, l, 4);
                l += __shfl_xor_sync(0xffffffffu, l, 8);
                l += __shfl_xor_sync(0xffffffffu, l, 16);
                row_acquire();
#pragma unroll
                for (int a = 0; a < 3; a++) {
                    row[64 * a + 16 * t + g] = st.acc[a][0] + st.acc[a][1];
                    row[64 * a + 16 * t + g + 8] = st.acc[a][2] + st.acc[a][3];
                }
                if (lane == 0) { row[192] = st.m; row[193] = l; }
                row_publish();
            } else if (kind == OP_RFLOAD) {
#pragma unroll 1
                for (uint32_t tile = (op >> 2) & 6u; tile <= ((op >> 2) | 1u); tile++) {
                    wait_tile(rpos);
                    const uint32_t base = slot0 + rpos * (8 * kSlotBytes);
#pragma unroll
                    for (int i = 0; i < 8; i++) {
                        if (tile == i) {
#pragma unroll
                            for (int k = 0; k < 6; k++) {
                                if (i & 1) ldsm4t(rf[i][k], (base + off[k >> 1]) ^ ((k & 1) << 6));
                                else ldsm4(rf[i][k], (base + off[k >> 1]) ^ ((k & 1) << 6));
                            }
                        }
                    }
                    ring_release();
                }
            } else if (kind == OP_QPROJ) {
                const uint32_t mask = (op >> 3) & 3u;
#pragma unroll 1
                for (uint32_t b = 0; b < 2; b++)
                    if ((mask >> b) & 1u) mbar_wait(sync0 + kBarXn + 8 * b, (op >> 5) & 1u);
                const uint32_t bb = mask == 3u ? (g & 1) : (mask >> 1);
                const uint32_t* xs = reinterpret_cast<const uint32_t*>(smem + kOffXn) + bb * 80 + 4 * w + t;
                float acc[3][4] = {};
#pragma unroll 1
                for (int p = 0; p < 3; p++) {
                    uint32_t xv = xs[p == 2 ? 48 : 32 * p];
                    if (p == 2 && w < 4) xv = 0u;
                    wait_tile(rpos);
                    const uint32_t base = sbase + rpos * 8 * kSlotBytes + w * 1024 + (lane & 7) * 128 +
                                          (((lane >> 3) ^ (lane & 7)) << 4);
#pragma unroll
                    for (int k = 0; k < 6; k++) {
                        uint32_t a[4];
                        ldsm4t(a, (base ^ ((k & 1) << 6)) + (k >> 1) * 8192);
                        mma16816(acc[k >> 1], a, (g >> 1) == 2 * (k & 1) ? xv : 0u, (g >> 1) == 2 * (k & 1) + 1 ? xv : 0u);
                    }
                    ring_release();
                }
#pragma unroll 1
                for (uint32_t b = 0; b < 2; b++) {
                    if (!((mask >> b) & 1u)) continue;
                    row_acquire();
#pragma unroll
                    for (int a = 0; a < 3; a++) {
                        row[64 * a + 16 * t + g] = b ? acc[a][1] : acc[a][0];
                        row[64 * a + 16 * t + g + 8] = b ? acc[a][3] : acc[a][2];
                    }
                    row_publish();
                }
            } else {
                const uint32_t mask = (op >> 3) & 3u;
                const uint32_t bb = mask == 3u ? (g & 1) : (mask >> 1);
                const uint32_t* ob = reinterpret_cast<const uint32_t*>(smem + kOffObf) + bb * 24 + t;
                const uint32_t roff = ((lane & 7) + 8 * (lane >> 4)) * 128 + ((((lane >> 3) & 1) ^ (lane & 7)) << 4);
                const bool ring = !(op >> 8);
                uint32_t sl[3];
#pragma unroll
                for (int p = 0; p < 3; p++) {
                    sl[p] = ring ? rpos : (op >> 8) + p;
                    if (ring && ++rpos == kRing) rpos = 0;
                }
                auto frag = [&](uint32_t (&a)[4], int p, int mt) {
                    ldsm4t(a, ((sbase + sl[p] * 8 * kSlotBytes + roff) ^ (((5 * w + mt) & 3) << 5)) + ((5 * w + mt) >> 2) * 2048);
                };
                uint32_t a0[5][4];
                wait_tile(sl[0]);
#pragma unroll
                for (int mt = 0; mt < 5; mt++) frag(a0[mt], 0, mt);
                if (ring) release(sl[0]);
                wait_tile(sl[1]);
                wait_tile(sl[2]);
                if (mask & 1u) mbar_wait(sync0 + kBarO, (op >> 5) & 1u);
                if (mask & 2u) mbar_wait(sync0 + kBarO + 8, (op >> 5) & 1u);
                TRACE_C(0);
                float c[3][4] = {};
#pragma unroll
                for (int p = 0; p < 3; p++) {
                    const uint32_t b0 = ob[8 * p], b1 = ob[8 * p + 4];
#pragma unroll
                    for (int mt = 0; mt < 5; mt++) {
                        if (p > 0) frag(a0[mt], p, mt);
                        const bool on = (g >> 1) == (mt & 3);
                        mma16816(c[mt == 4 ? 2 : (mt & 1)], a0[mt], on ? b0 : 0u, on ? b1 : 0u);
                    }
                    if (p > 0 && ring) release(sl[p]);
                }
                TRACE_C(1);
                row_acquire();
                TRACE_C(2);
                row[16 * t + g] = c[0][0] + c[1][0]; row[80 + 16 * t + g] = c[0][1] + c[1][1];
                row[16 * t + g + 8] = c[0][2] + c[1][2]; row[80 + 16 * t + g + 8] = c[0][3] + c[1][3];
                if (t == 0) {
                    row[64 + g] = c[2][0]; row[144 + g] = c[2][1];
                    row[72 + g] = c[2][2]; row[152 + g] = c[2][3];
                }
                __syncwarp();
#pragma unroll 1
                for (uint32_t b = 0; b < 2; b++)
                    if (((mask >> b) & 1u) && lane < 27) {
                        const float* y = row + 80 * b + 3 * lane;
                        float4* dst = ((op >> 5) & 3u) == 3u ? g_out[b][cta % kOutReplicas] : g_acc[b][(op >> 5) & 3u];
                        red_packet(dst + 27 * w + lane, y[0], y[1], lane < 26 ? y[2] : 0.f);
                    }
                TRACE_C(3);
                __syncwarp();
                if (lane < 2 && ((mask >> lane) & 1u)) mbar_arrive(sync0 + kBarSentY + 8 * lane);
            }
        }
    } else {
        asm volatile("setmaxnreg.dec.sync.aligned.u32 40;");
        if (w == 8) {
            const int rowA = (h * 4096 + 3072 + 256 * jq) * 3, rowB = (h * 4096 + 1024 * jq) * 3;
            const int rowWq = 160 * jq, rowWo = 192 * h + 48 * jq;
            const uint32_t tau = P.tau, tauLow = P.tauLow, tauW = P.tauW, credit = P.credit;
            const uint32_t winLow = P.winLow, winHigh = P.winHigh;
            const uint64_t polKeep = make_policy(true), polStream = make_policy(false);
            uint32_t fifo = 0, queued = 0, stale = 0, par = 0, nfl = 0, next = now_ns() - P.credit0;
            auto coord = [&](uint32_t e) {
                return (int)((e >> 10) & 0x7ffffu) + ((e & 4u) ? ((e & 2u) ? rowWo : rowWq) : ((e & 2u) ? rowB : rowA));
            };
            auto interval = [&](uint32_t e) { return (e & 4u) ? tauW : ((e & LD_LOW) ? tauLow : tau); };
            uint32_t recent = 0;
            uint32_t e = P.loads[0], m = 0;
#pragma unroll 1
            for (uint32_t n = 0; e & LD_VALID; n++) {
                const uint32_t enext = P.loads[n + 1];
                const uint32_t s = (e >> 4) & 15u;
                const int c1 = coord(e), c2 = ((e >> 1) & 3u) == 2u ? 3 * h : 0;
                if (m < n) m = n;
                for (uint32_t it = 0; !mbar_test(sbase + kOffEmpty + 8 * s, ((par >> s) & 1u) ^ 1u); it++) {
                    if (it > 16 * kSpinLimit) __trap();
                    const uint32_t f = P.loads[m], now = now_ns();
                    const uint32_t o = (recent >> (4 * P.lookBack)) & 15u;
                    if (m < n + P.look && (f & LD_VALID) && (int)(now - next - P.lookDelay) >= 0 &&
                        mbar_test(sbase + kOffFull + 8 * o, ((par >> o) & 1u) ^ 1u)) {
                        if (!(f & LD_HIT)) {
                            if (elect()) tma3d_prefetch(&P.tm[f & 7u], 0, coord(f), ((f >> 1) & 3u) == 2u ? 3 * h : 0, polStream);
                            next = now - P.lookDelay + interval(f);
                        }
                        m++;
                    }
                }
                stale |= queued & (1u << s);
                queued &= ~(1u << s);
                if (!(e & LD_HIT) && n >= m) {
                    for (const uint32_t win = (e & LD_LOW) ? winLow : winHigh; nfl >= win; nfl--) {
                        const uint32_t o = (fifo >> (4 * nfl - 4)) & 15u;
                        if ((stale >> o) & 1u) {
                            stale ^= 1u << o;
                        } else {
                            mbar_wait_u(sbase + kOffFull + 8 * o, ((par >> o) & 1u) ^ 1u);
                            queued ^= 1u << o;
                        }
                    }
                    if (e & LD_ANCHOR)
                        next = __shfl_sync(0xffffffffu, *reinterpret_cast<volatile uint32_t*>(smem + kOffAnchor), 0) + P.anchorDelay;
                    uint32_t now = now_ns();
                    while ((int)(now - next) < 0) now = now_ns();
                    if (n >= 4 && (int)(now - credit - next) > 0) next = now - credit;
                    next += interval(e);
                    fifo = (fifo << 4) | s;
                    queued |= 1u << s;
                    nfl++;
                }
                if (elect()) {
                    mbar_expect(sbase + kOffFull + 8 * s, (e & 6u) == 6u ? 20480 : 8 * kSlotBytes);
                    tma3d(sbase + s * 8 * kSlotBytes, &P.tm[e & 7u], 0, c1, c2, sbase + kOffFull + 8 * s, polStream);
                    if (e & LD_KEEP) tma3d_prefetch(&P.tm[e & 7u], 0, c1, c2, polKeep);
                }
                par ^= 1u << s;
                recent = (recent << 4) | s;
                e = enext;
            }
        } else {
            if (w == 9) {
#pragma unroll 1
                for (int n = 0;; n++) {
                    const uint32_t job = P.merge[n];
                    if ((job & 3u) == MG_END) break;
                    const uint32_t b = (job >> 2) & 1u;
                    const uint32_t tag = 1 + ((job >> 3) & 3u);
                    mbar_wait(sync0 + kBarRows, n & 1);
                    if ((job & 3u) == MG_Q) {
#pragma unroll 1
                        for (int u = lane; u < 40; u += 32) {
                            float o[5] = {};
#pragma unroll
                            for (int i = 0; i < 8; i++)
#pragma unroll
                                for (int k = 0; k < 5; k++) o[k] += wbuf[i * kWRow + 5 * min(u, 38) + k];
                            st_packet5(&g_q[b][h][jq][u], o, tag);
                        }
                        __syncwarp();
                        if (lane == 0) mbar_arrive(sync0 + kBarSentQ + 8 * b);
                    } else {
                        float* cp = reinterpret_cast<float*>(smem + kOffCpart) + b * kWRow;
                        const bool merge = !(job & 32u);
                        float mi = -INFINITY, li = 0.f;
                        if (lane < 8) { mi = wbuf[lane * kWRow + 192]; li = wbuf[lane * kWRow + 193]; }
                        else if (lane == 8 && merge) { mi = cp[192]; li = cp[193]; }
                        float M = mi;
#pragma unroll
                        for (int o = 8; o > 0; o >>= 1) M = fmaxf(M, __shfl_xor_sync(0xffffffffu, M, o));
                        M = __shfl_sync(0xffffffffu, M, 0);
                        const float sc = ex2((mi - M) * kLog2e);
                        const float L = warp_sum(li * sc);
                        const float ps = __shfl_sync(0xffffffffu, sc, 8);
                        float o[2][3];
#pragma unroll
                        for (int r = 0; r < 2; r++)
#pragma unroll
                            for (int k = 0; k < 3; k++) o[r][k] = merge ? cp[3 * (lane + 32 * r) + k] * ps : 0.f;
#pragma unroll
                        for (int i = 0; i < 8; i++) {
                            const float si = __shfl_sync(0xffffffffu, sc, i);
#pragma unroll
                            for (int r = 0; r < 2; r++)
#pragma unroll
                                for (int k = 0; k < 3; k++)
                                    o[r][k] = fmaf(wbuf[i * kWRow + 3 * (lane + 32 * r) + k], si, o[r][k]);
                        }
                        if (job & 64u) {
#pragma unroll
                            for (int r = 0; r < 2; r++)
                                st_packet(&g_p[b][h][(lane >> 4) + 2 * r][jq][lane & 15], o[r][0], o[r][1], o[r][2], tag);
                            if (lane < 8) st_packet(&g_p[b][h][lane >> 1][jq][16 + (lane & 1)], M, L, 0.f, tag);
                            if (lane == 0) mbar_arrive(sync0 + kBarSentP + 8 * b);
                        } else {
#pragma unroll
                            for (int r = 0; r < 2; r++)
#pragma unroll
                                for (int k = 0; k < 3; k++) cp[3 * (lane + 32 * r) + k] = o[r][k];
                            if (lane == 0) { cp[192] = M; cp[193] = L; }
                        }
                    }
                    __syncwarp();
                    if (lane == 0) mbar_arrive(sync0 + kBarFree);
                }
            } else {
                const uint32_t b = w - 10;
                __nv_bfloat16* const xn = reinterpret_cast<__nv_bfloat16*>(smem + kOffXn) + b * 160;
                __nv_bfloat16* const qd = reinterpret_cast<__nv_bfloat16*>(smem + kOffQf) + b * 192;
                __nv_bfloat16* const ob = reinterpret_cast<__nv_bfloat16*>(smem + kOffObf) + b * 48;
#pragma unroll 1
                for (uint32_t layer = 0; layer < 4; layer++) {
                    const uint32_t tag = layer + 1;
                    int lane = threadIdx.x & 31;
                    asm volatile("" : "+r"(lane));
                    {
                        uint32_t x01[7], x2[7];
                        if (layer == 0) {
#pragma unroll
                            for (int i = 0; i < 7; i++) {
                                const int p = lane + 32 * i, u = p % 27;
                                const unsigned short* xp = reinterpret_cast<const unsigned short*>(P.x) + b * 640 + (p / 27) * 80 + 3 * u;
                                x01[i] = p < kAccPackets ? xp[0] | ((uint32_t)xp[1] << 16) : 0u;
                                x2[i] = (p < kAccPackets && u < 26) ? xp[2] : 0u;
                            }
                        } else {
                            mbar_wait(sync0 + kBarSentY + 8 * b, (layer - 1) & 1);
                            TRACE_G(4 * layer - 1);
                            uint4 v[7];
                            const uint4* src = reinterpret_cast<const uint4*>(&g_acc[b][layer - 1][lane]);
                            const uint32_t done = __float_as_uint(kAccDone);
                            POLL_UNTIL(v[0] = ld_packet(src - lane + 27 * (cta & 7) + min(lane, 26)), v[0].w == done);
                            POLL_UNTIL(
                                v[0] = ld_packet(src); v[1] = ld_packet(src + 32); v[2] = ld_packet(src + 64);
                                v[3] = ld_packet(src + 96); v[4] = ld_packet(src + 128); v[5] = ld_packet(src + 160);
                                v[6] = ld_packet(src + (lane < 24 ? 192 : 0)),
                                v[0].w == done && v[1].w == done && v[2].w == done && v[3].w == done && v[4].w == done &&
                                    v[5].w == done && v[6].w == done);
#pragma unroll
                            for (int i = 0; i < 7; i++) {
                                x01[i] = pack_bf16(__uint_as_float(v[i].x), __uint_as_float(v[i].y));
                                x2[i] = pack_bf16(__uint_as_float(v[i].z), 0.f);
                            }
                            if (lane >= 24) x01[6] = x2[6] = 0u;
                        }
                        TRACE_G(16 + 4 * layer);
                        float sum = 0.f;
#pragma unroll
                        for (int i = 0; i < 7; i++) sum += (bf_lo(x01[i]) + bf_hi(x01[i])) + bf_lo(x2[i]);
                        const float mean = warp_sum(sum) * (1.f / 640.f);
                        float sq = 0.f;
#pragma unroll
                        for (int i = 0; i < 7; i++) {
                            const bool none = i == 6 && lane >= 24;
                            const float d0 = none ? 0.f : bf_lo(x01[i]) - mean, d1 = none ? 0.f : bf_hi(x01[i]) - mean;
                            const bool last = lane == 26 - 5 * i || lane == 53 - 5 * i;
                            const float d2 = (none || last) ? 0.f : bf_lo(x2[i]) - mean;
                            sq += fmaf(d0, d0, fmaf(d1, d1, d2 * d2));
                        }
                        const float var = warp_sum(sq) * (1.f / 640.f);
                        const float meanb = bf16r(mean);
                        const float rden = __fdividef(1.f, bf16r(fast_sqrt(bf16r(bf16r(var) + 1e-5f))));
#pragma unroll
                        for (int i = 0; i < 7; i++) {
                            const uint32_t q = lane + 32 * i - 54 * jq;
                            if (q < 54u) {
                                const int c = 3 * q - (q >= 27u);
                                xn[c] = __float2bfloat16_rn(bf16r(bf_lo(x01[i]) - meanb) * rden);
                                xn[c + 1] = __float2bfloat16_rn(bf16r(bf_hi(x01[i]) - meanb) * rden);
                                if (q != 26u && q != 53u) xn[c + 2] = __float2bfloat16_rn(bf16r(bf_lo(x2[i]) - meanb) * rden);
                            }
                        }
                        if (lane == 0) *reinterpret_cast<volatile uint32_t*>(smem + kOffAnchor) = now_ns();
                        __syncwarp();
                        if (lane == 0) mbar_arrive(sync0 + kBarXn + 8 * b);
                        TRACE_G(4 * layer);
#pragma unroll
                        for (int i = 0; i < 7; i++) {
                            const int p = lane + 32 * i;
                            if ((p & 127) == cta && p < kAccPackets) {
                                red_packet((layer == 3 ? g_out[b][0] : g_acc[b][layer]) + p, bf_lo(x01[i]), bf_hi(x01[i]), bf_lo(x2[i]));
                                if (layer >= 2) g_acc[b][layer - 2][p] = make_float4(0.f, 0.f, 0.f, 0.f);
                            }
                        }
                    }
                    {
                        mbar_wait(sync0 + kBarSentQ + 8 * b, layer & 1);
                        uint4 v[5];
                        const uint4* src = &g_q[b][h][0][lane];
                        const uint4* ext = &g_q[b][h][lane & 3][lane < 28 ? 32 + (lane >> 2) : 38];
                        POLL_UNTIL(
                            v[0] = ld_packet(src); v[1] = ld_packet(src + 40); v[2] = ld_packet(src + 80);
                            v[3] = ld_packet(src + 120); v[4] = ld_packet(ext),
                            (v[0].w >> 24) == tag && (v[1].w >> 24) == tag && (v[2].w >> 24) == tag &&
                                (v[3].w >> 24) == tag && (v[4].w >> 24) == tag);
                        __syncwarp();
                        TRACE_G(16 + 4 * layer + 1);
                        auto store_q = [&](int d, float q) {
                            qd[(d & ~31) + ((d >> 3) & 1) * 16 + ((d >> 1) & 3) * 4 + ((d >> 4) & 1) * 2 + (d & 1)] =
                                __float2bfloat16_rn(q);
                        };
                        float a[5] = {};
#pragma unroll
                        for (int i = 0; i < 4; i++) add_packet5(a, v[i]);
#pragma unroll
                        for (int k = 0; k < 5; k++) store_q(5 * lane + k, a[k]);
                        float e[5] = {};
                        add_packet5(e, v[4]);
#pragma unroll
                        for (int k = 0; k < 5; k++) {
                            e[k] += __shfl_xor_sync(0xffffffffu, e[k], 1);
                            e[k] += __shfl_xor_sync(0xffffffffu, e[k], 2);
                            const int d = 160 + 5 * (lane >> 2) + k;
                            if ((lane & 3) == 0 && d < 192) store_q(d, e[k]);
                        }
                        __syncwarp();
                        if (lane == 0) mbar_arrive(sync0 + kBarQ + 8 * b);
                        TRACE_G(4 * layer + 1);
                    }
                    if (P.exp) break;
                    {
                        mbar_wait(sync0 + kBarSentP + 8 * b, layer & 1);
                        uint4 v0, v1, ml;
                        const uint4* src = &g_p[b][h][jq][2 * (lane >> 4)][lane & 15];
                        const uint4* mls = &g_p[b][h][jq][lane & 3][16];
                        POLL_UNTIL(v0 = ld_packet(src); v1 = ld_packet(src + 18); ml = ld_packet(mls),
                                   v0.w == tag && v1.w == tag && ml.w == tag);
                        __syncwarp();
                        TRACE_G(16 + 4 * layer + 2);
                        const float mi = __uint_as_float(ml.x);
                        float M = fmaxf(mi, __shfl_xor_sync(0xffffffffu, mi, 1));
                        M = fmaxf(M, __shfl_xor_sync(0xffffffffu, M, 2));
                        const float sc = ex2((mi - M) * kLog2e);
                        float L = __uint_as_float(ml.y) * sc;
                        L += __shfl_xor_sync(0xffffffffu, L, 1);
                        L += __shfl_xor_sync(0xffffffffu, L, 2);
                        const float s0 = __shfl_sync(0xffffffffu, sc, 2 * (lane >> 4));
                        const float s1 = __shfl_sync(0xffffffffu, sc, 2 * (lane >> 4) + 1);
                        float o0 = fmaf(__uint_as_float(v0.x), s0, __uint_as_float(v1.x) * s1);
                        float o1 = fmaf(__uint_as_float(v0.y), s0, __uint_as_float(v1.y) * s1);
                        float o2 = fmaf(__uint_as_float(v0.z), s0, __uint_as_float(v1.z) * s1);
                        o0 += __shfl_xor_sync(0xffffffffu, o0, 16);
                        o1 += __shfl_xor_sync(0xffffffffu, o1, 16);
                        o2 += __shfl_xor_sync(0xffffffffu, o2, 16);
                        if (lane < 16) {
                            ob[3 * lane] = __float2bfloat16_rn(__fdividef(o0, L));
                            ob[3 * lane + 1] = __float2bfloat16_rn(__fdividef(o1, L));
                            ob[3 * lane + 2] = __float2bfloat16_rn(__fdividef(o2, L));
                        }
                        __syncwarp();
                        if (lane == 0) mbar_arrive(sync0 + kBarO + 8 * b);
                        TRACE_G(4 * layer + 2);
                    }
                }
                if (!P.exp) {
                    mbar_wait(sync0 + kBarSentY + 8 * b, 1);
                    const int p = cta + 128 * ((lane >> 3) & 1), r = lane & 7;
                    float4* src = &g_out[b][r][p < kAccPackets ? p : cta];
                    const float want = kCtas / kOutReplicas + (r == 0);
                    uint4 v;
                    for (uint32_t it = 0;; it++) {
                        v = ld_packet(reinterpret_cast<const uint4*>(src));
                        if (__all_sync(0xffffffffu, v.w == __float_as_uint(want))) break;
                        if (it > kSpinLimit) __trap();
                    }
                    float o0 = __uint_as_float(v.x), o1 = __uint_as_float(v.y), o2 = __uint_as_float(v.z);
#pragma unroll
                    for (int o = 1; o < 8; o <<= 1) {
                        o0 += __shfl_xor_sync(0xffffffffu, o0, o);
                        o1 += __shfl_xor_sync(0xffffffffu, o1, o);
                        o2 += __shfl_xor_sync(0xffffffffu, o2, o);
                    }
                    if (lane < 16 && p < kAccPackets) {
                        if (r < 3 - (p % 27 == 26))
                            P.out[b * 640 + (p / 27) * 80 + 3 * (p % 27) + r] = __float2bfloat16_rn(r == 0 ? o0 : r == 1 ? o1 : o2);
                        *src = make_float4(0.f, 0.f, 0.f, 0.f);
                        if (r == 0) g_acc[b][2][p] = make_float4(0.f, 0.f, 0.f, 0.f);
                    }
                    TRACE_G(15);
                }
            }
        }
    }
}

struct Sched {
    Params& P;
    int np = 0, nm = 0, nl = 0, rslot = 0, mark = 0;
    uint32_t pending = 0;
    enum { RF = 1 << 7, FIRST = 1 << 11, PUB = 1 << 12 };
    void low_begin(int back) { mark = nl - back; }
    void low_end(int back) { for (int i = mark; i < nl - back; i++) P.loads[i] |= LD_LOW; }
    void slot(uint32_t e, int s) { P.loads[nl++] = e | (s << 4); }
    void ring(uint32_t e) {
        slot(e | pending, rslot);
        pending = 0;
        rslot = (rslot + 1) % kRing;
    }
    static uint32_t tile(int isB, int b, int idx, int v) {
        return LD_VALID | (2 * isB + v) | (uint32_t)((b * 32 * 4096 + 64 * idx) * 3) << 10;
    }
    static uint32_t wq(int layer, int p) { return LD_VALID | (4 + (layer & 1)) | (p == 2 ? 96 : 64 * p) << 10; }
    static uint32_t wo(int layer, int p) { return LD_VALID | (6 + (layer & 1)) | (16 * p) << 10; }
    void kv(int isB, int b, int idx, uint32_t fk = 0, uint32_t fv = 0) {
        ring(tile(isB, b, idx, 0) | fk);
        ring(tile(isB, b, idx, 1) | fv);
    }
    void ret(int b, int idx, int pair) {
        slot(tile(1, b, idx, 0), kRing + 2 * pair);
        slot(tile(1, b, idx, 1), kRing + 2 * pair + 1);
    }
    void qproj(int mask, int layer, uint32_t f = 0, bool anchor = true) {
        for (int p = 0; p < 3; p++) ring(wq(layer, p) | f);
        if (anchor) pending = LD_ANCHOR;
        P.prog[np++] = OP_QPROJ | (mask << 3) | (layer << 5);
        for (int b = 0; b < 2; b++)
            if ((mask >> b) & 1) P.merge[nm++] = MG_Q | (b << 2) | (layer << 3);
    }
    void oproj(int mask, int layer, uint32_t f = 0, int firstSlot = 0) {
        if (!firstSlot) for (int p = 0; p < 3; p++) ring(wo(layer, p) | f);
        P.prog[np++] = OP_OPROJ | (mask << 3) | (layer << 5) | (firstSlot << 8);
    }
    void rfload(int pair, int isB, int b, int idx) {
        kv(isB, b, idx);
        P.prog[np++] = OP_RFLOAD | (pair << 3);
    }
    void seg(int b, int layer, uint32_t flags, const char* order, int nrel = 0) {
        uint32_t seq = 0;
        int n = 0;
        for (; order[n]; n++) if (order[n] == 'r') seq |= 1u << n;
        seq |= 1u << n;
        P.prog[np++] = OP_SEG | (b << 3) | ((layer & 1) << 4) | (flags & RF) | (nrel << 8) | (seq << 10);
        P.merge[nm++] = MG_ATTN | (b << 2) | (layer << 3) | ((flags & FIRST) ? 32 : 0) | ((flags & PUB) ? 64 : 0);
    }
    void seg(int b, int layer, uint32_t flags, int nring) { seg(b, layer, flags, &"dddddddddddddddd"[16 - nring]); }
};

const char* tune_str(const char* name, const char* dflt) {
    (void)name;
    return dflt;
}

int tune(const char* name, int dflt) {
    (void)name;
    return dflt;
}

void build_schedule(Params& P) {
    for (int i = 0; i < kMaxProg; i++) P.prog[i] = P.merge[i] = 0;
    for (int i = 0; i < kMaxLoads; i++) P.loads[i] = LD_NONE;
    P.winLow = tune("WINLOW", 3);
    P.winHigh = tune("WINHIGH", 3);
    P.tau = tune("TAU", 980);
    P.tauLow = tune("TAULOW", 1000);
    P.tauW = tune("TAUW", P.tauLow * 5 / 6);
    P.credit = tune("CREDIT", 500);
    P.anchorDelay = tune("ADELAY", 0);
    P.credit0 = tune("CREDIT0", 1500);
    P.look = tune("LOOK", 4);
    P.lookDelay = tune("LOOKDELAY", 0);
    P.lookBack = tune("LOOKBACK", 1);

    Sched S{P};
    using F = Sched;
    const int keep[2] = {tune("KEEP0", 10), tune("KEEP1", 10)};
    auto flag = [&](int b, int idx, int v, uint32_t f) { return (2 * (15 - idx) + (1 - v)) < keep[b] ? f : 0u; };
    const int hit[2] = {16 - (keep[0] + 1) / 2, 16 - (keep[1] + 1) / 2};
    int next0 = 3, next1 = 7, nextA = 0;
    auto first0 = [&](const char* order, uint32_t flags) {
        for (const char* c = order; *c; c++)
            if (*c != 'r') { S.kv(1, 0, next0, flag(0, next0, 0, LD_KEEP), flag(0, next0, 1, LD_KEEP)); next0++; }
        S.seg(0, 1, flags, order);
    };
    auto fillA = [&](const char* order, uint32_t flags) {
        int nr = 0;
        for (const char* c = order; *c; c++) if (*c == 'r') nr++; else S.kv(0, 1, nextA++);
        S.seg(1, 0, flags, order, nr);
    };
    auto fill0 = [&](int n, uint32_t flags = 0) {
        int c = 0;
        for (; c < n && next0 < hit[0]; c++) S.kv(1, 0, next0++);
        if (c > 0 || flags) S.seg(0, 3, flags, c);
    };
    auto fill1 = [&](int n) {
        int c = 0;
        const uint32_t flags = next1 == 7 ? F::FIRST : 0;
        for (; c < n && next1 < hit[1]; c++) S.kv(1, 1, next1++);
        if (c > 0) S.seg(1, 1, flags, c);
    };
    auto second_pass = [&](int b, int& nextD, const char* order, int rb, int rbase, int lead) {
        int nextH = hit[b], total = 0, tiles = 0, done = 0;
        for (const char* c = order; *c; c++) if (*c != 'r') total += 2;
        auto refill = [&]() { S.slot(F::tile(1, rb, rbase + done / 2, done & 1), kRing + done); done++; };
        for (const char* c = order; *c; c++) {
            if (*c == 'r') continue;
            const int idx = *c == 'h' ? nextH++ : nextD++;
            for (int v = 0; v < 2; v++, tiles++) {
                while (tiles >= kRing && done < 6 && (done < lead || (done - lead + 1) * (total - kRing) <= (tiles - kRing) * (7 - lead)))
                    refill();
                S.ring(F::tile(1, b, idx, v) | flag(b, idx, v, LD_HIT));
            }
        }
        while (done < 6) refill();
    };

    P.exp = tune("EXP", 0);
    if (P.exp) {
        S.qproj(3, 0);
        for (int r = 0; r < 2; r++)
            for (int b = 0; b < 2; b++) {
                for (int i = 0; i < 15; i++) S.kv(1, b, i);
                S.seg(b, 0, F::FIRST, 15);
            }
        return;
    }
    const int lb = tune("LOWBACK", 0);
    const int early = tune("EARLY", 0);
    S.qproj(3, 0, 0, false);
    for (int i = 0; i < early; i++) {
        S.slot(F::tile(0, 1, i, 0), kRing + 2 * i);
        S.slot(F::tile(0, 1, i, 1), kRing + 2 * i + 1);
    }
    for (int i = 0; i < 4; i++) S.rfload(i, 0, 0, i);
    S.seg(0, 0, F::RF | F::FIRST | F::PUB, 0);
    S.low_begin(lb);
    if (tune("JOINT", 1)) {
        nextA = early;
        fillA(tune_str("LA", "dddd"), F::FIRST | F::PUB);
        S.oproj(3, 0);
        for (int i = 0; i < 3; i++) S.ret(0, i, i);
        S.qproj(3, 1);
        S.low_end(0);
        first0("dddrdddrdddrdddd", F::FIRST | F::PUB);
    } else {
        nextA = early;
        fillA(tune_str("LA1", "d"), F::FIRST);
        S.oproj(1, 0, LD_KEEP);
        fillA(tune_str("LA2", "ddd"), F::PUB);
        S.qproj(1, 1, LD_KEEP);
        S.pending = 0;
        P.loads[S.nl] = 0;
        S.ret(0, 0, 0);
        P.loads[S.nl - 2] |= tune("RETANCHOR", 0) ? LD_ANCHOR : 0;
        S.oproj(2, 0, LD_HIT);
        S.ret(0, 1, 1);
        S.ret(0, 2, 2);
        first0(tune_str("L2A", "ddd"), F::FIRST);
        S.qproj(2, 1, LD_HIT);
        S.low_end(0);
        first0(tune_str("L2B", "drddrddrddddd"), F::PUB);
    }
    next0 = 3;
    S.low_begin(lb);
    fill1(tune("F21", 1));
    S.oproj(1, 1);
    fill1(tune("F22", 2));
    S.qproj(1, 2);
    fill1(tune("F23", 1));
    S.seg(0, 2, F::RF | F::FIRST | F::PUB, 0);
    const int r1 = tune("R31", 1), r2 = r1 + tune("R32", 2);
    for (int i = 0; i < r1; i++) S.rfload(i, 1, 1, 3 + i);
    fill1(tune("F31", 0));
    S.oproj(1, 2);
    for (int i = r1; i < r2; i++) S.rfload(i, 1, 1, 3 + i);
    fill1(tune("F32", 0));
    S.qproj(1, 3);
    for (int i = r2; i < 4; i++) S.rfload(i, 1, 1, 3 + i);
    fill1(16);
    S.low_end(0);
    const char* t4 = tune_str("T4", "rrhrhhhh");
    second_pass(0, next0, t4, 1, 0, tune("LEAD4", 2));
    S.seg(0, 3, F::FIRST, t4, 3);
    for (int i = hit[1]; i < 16; i++) S.kv(1, 1, i, flag(1, i, 0, LD_KEEP), flag(1, i, 1, LD_KEEP));
    S.seg(1, 1, F::RF | F::PUB, tune_str("T4B", "ddrdrrdd"));
    S.low_begin(lb);
    fill0(tune("F41", 1));
    S.oproj(2, 1);
    fill0(tune("F42", 2));
    S.qproj(2, 2);
    fill0(tune("F43", 1));
    for (int i = 0; i < 4; i++) S.kv(0, 1, i);
    S.seg(1, 2, F::FIRST | F::PUB, 4);
    fill0(tune("F51", 1));
    S.oproj(2, 2);
    fill0(tune("F52", 2));
    S.qproj(2, 3);
    fill0(16, F::PUB);
    S.low_end(0);
    const char* t6 = tune_str("T6", "rrdrhhhrhrhr");
    int nextD = 10;
    second_pass(1, nextD, t6, 1, 7, tune("LEAD6", 2));
    S.seg(1, 3, F::RF | F::FIRST | F::PUB, t6, 3);
    S.oproj(3, 3);
}

typedef CUresult (*EncodeFn)(CUtensorMap*, CUtensorMapDataType, cuuint32_t, void*, const cuuint64_t*,
                             const cuuint64_t*, const cuuint32_t*, const cuuint32_t*, CUtensorMapInterleave,
                             CUtensorMapSwizzle, CUtensorMapL2promotion, CUtensorMapFloatOOBfill);

}

extern "C" void kernel_launch(void* const* d_in, const int* in_sizes, int n_in, void* d_out, int out_size) {
    (void)in_sizes; (void)n_in; (void)out_size;
    Params P;
    void* fn = nullptr;
    cudaDriverEntryPointQueryResult qr;
    cudaGetDriverEntryPoint("cuTensorMapEncodeTiled", &fn, cudaEnableDefault, &qr);
    EncodeFn encode = reinterpret_cast<EncodeFn>(fn);
    const CUtensorMapL2promotion promo = (CUtensorMapL2promotion)tune("PROMO", CU_TENSOR_MAP_L2_PROMOTION_NONE);
    void* kv[4] = {d_in[1], d_in[2], d_in[6], d_in[7]};
    for (int i = 0; i < 4; i++) {
        const cuuint64_t dims[3] = {64, 2ull * 32 * 4096 * 3, 1};
        const cuuint64_t strides[2] = {128, 2ull * 32 * 4096 * 3 * 128};
        const cuuint32_t box[3] = {64, 192, 1};
        const cuuint32_t es[3] = {1, 1, 1};
        encode(&P.tm[i], CU_TENSOR_MAP_DATA_TYPE_BFLOAT16, 3, kv[i], dims, strides, box, es,
               CU_TENSOR_MAP_INTERLEAVE_NONE, CU_TENSOR_MAP_SWIZZLE_128B, promo, CU_TENSOR_MAP_FLOAT_OOB_FILL_NONE);
    }
    void* wq[2] = {d_in[3], d_in[8]};
    for (int i = 0; i < 2; i++) {
        const cuuint64_t dims[3] = {64, 640, 96};
        const cuuint64_t strides[2] = {12288, 128};
        const cuuint32_t box[3] = {64, 64, 3};
        const cuuint32_t es[3] = {1, 1, 1};
        encode(&P.tm[4 + i], CU_TENSOR_MAP_DATA_TYPE_BFLOAT16, 3, wq[i], dims, strides, box, es,
               CU_TENSOR_MAP_INTERLEAVE_NONE, CU_TENSOR_MAP_SWIZZLE_128B, promo, CU_TENSOR_MAP_FLOAT_OOB_FILL_NONE);
    }
    void* wo[2] = {d_in[4], d_in[9]};
    for (int i = 0; i < 2; i++) {
        const cuuint64_t dims[3] = {64, 6144, 10};
        const cuuint64_t strides[2] = {1280, 128};
        const cuuint32_t box[3] = {64, 16, 10};
        const cuuint32_t es[3] = {1, 1, 1};
        encode(&P.tm[6 + i], CU_TENSOR_MAP_DATA_TYPE_BFLOAT16, 3, wo[i], dims, strides, box, es,
               CU_TENSOR_MAP_INTERLEAVE_NONE, CU_TENSOR_MAP_SWIZZLE_128B, promo, CU_TENSOR_MAP_FLOAT_OOB_FILL_NONE);
    }
    P.x = static_cast<const __nv_bfloat16*>(d_in[0]);
    P.out = static_cast<__nv_bfloat16*>(d_out);
    build_schedule(P);
    cudaFuncSetAttribute(fused_decode_kernel, cudaFuncAttributeMaxDynamicSharedMemorySize, kSmemBytes);
    fused_decode_kernel<<<kCtas, kThreads, kSmemBytes>>>(P);
}
```

```cpp
#include <cuda_runtime.h>
#include <cuda_bf16.h>
#include <cuda.h>
#include <stdint.h>

namespace {

constexpr int kCtas = 128;
constexpr int kThreads = 384;
constexpr int kSlotBytes = 3072;
constexpr int kRing = 3;
constexpr int kSlots = 9;
constexpr int kWRow = 196;

constexpr int kOffWbuf = kSlots * 8 * kSlotBytes;
constexpr int kOffCpart = kOffWbuf + 8 * kWRow * 4;
constexpr int kOffQf = kOffCpart + 2 * kWRow * 4;
constexpr int kOffXn = kOffQf + 2 * 96 * 4;
constexpr int kOffObf = kOffXn + 2 * 160 * 2;
constexpr int kOffFull = kOffObf + 2 * 48 * 2;
constexpr int kOffEmpty = kOffFull + kSlots * 8;
constexpr int kOffSync = kOffEmpty + kSlots * 8;
constexpr int kOffAnchor = kOffSync + 14 * 8;
constexpr int kSmemBytes = kOffAnchor + 8;
static_assert(kSmemBytes <= 232448, "shared memory budget");
constexpr int kBarRows = 0, kBarFree = 8, kBarQ = 16, kBarXn = 32, kBarO = 48;
constexpr int kBarSentQ = 64, kBarSentP = 80, kBarSentY = 96;

constexpr int kMaxProg = 112;
constexpr int kMaxLoads = 200;

enum : uint32_t { OP_END = 0, OP_QPROJ = 1, OP_RFLOAD = 2, OP_SEG = 3, OP_OPROJ = 4 };
enum : uint32_t { LD_NONE = 0, LD_KEEP = 1u << 3, LD_LOW = 1u << 8, LD_VALID = 1u << 9, LD_ANCHOR = 1u << 29, LD_FAR = 1u << 30, LD_HIT = 1u << 31 };
enum : uint32_t { MG_END = 0, MG_ATTN = 1, MG_Q = 2 };

struct alignas(64) Params {
    CUtensorMap tm[8];
    const __nv_bfloat16* x;
    __nv_bfloat16* out;
    uint32_t winLow, winHigh;
    uint32_t tau, tauLow, tauW, credit;
    uint32_t look, lookBack, lookFar, hitTouch, nStart, winStart;
    uint32_t anchorDelay, startDelay;
    uint32_t exp;
    uint32_t prog[kMaxProg];
    uint32_t merge[kMaxProg];
    uint32_t loads[kMaxLoads];
};

__device__ uint4 g_q[2][32][4][40];
__device__ uint4 g_p[2][32][4][4][18];
constexpr int kAccPackets = 216;
constexpr float kAccDone = 129.f;
__device__ float4 g_acc[2][3][kAccPackets];
constexpr int kOutReplicas = 8;
__device__ float4 g_out[2][kOutReplicas][kAccPackets];

#define SPINNS 30
#define SLEEPNS 200
#define POLL_SLEEP __nanosleep(SLEEPNS)
constexpr uint32_t kSpinLimit = 1u << 22;

__device__ __forceinline__ void mbar_init(uint32_t bar, uint32_t count) {
    asm volatile("mbarrier.init.shared::cta.b64 [%0], %1;" ::"r"(bar), "r"(count) : "memory");
}
__device__ __forceinline__ void mbar_arrive(uint32_t bar) {
    asm volatile("mbarrier.arrive.shared::cta.b64 _, [%0];" ::"r"(bar) : "memory");
}
__device__ __forceinline__ bool mbar_test(uint32_t bar, uint32_t parity) {
    uint32_t ok;
    asm volatile(
        "{\n\t.reg .pred p;\n\t"
        "mbarrier.test_wait.parity.shared::cta.b64 p, [%1], %2;\n\t"
        "selp.u32 %0, 1, 0, p;\n\t}"
        : "=r"(ok) : "r"(bar), "r"(parity) : "memory");
    return __all_sync(0xffffffffu, ok);
}
__device__ __forceinline__ void mbar_expect(uint32_t bar, uint32_t bytes) {
    asm volatile("mbarrier.arrive.expect_tx.shared::cta.b64 _, [%0], %1;" ::"r"(bar), "r"(bytes) : "memory");
}
__device__ __forceinline__ void mbar_wait(uint32_t bar, uint32_t parity) {
    uint32_t ok, it = 0;
    do {
        asm volatile(
            "{\n\t.reg .pred p;\n\t"
            "mbarrier.try_wait.parity.shared::cta.b64 p, [%1], %2;\n\t"
            "selp.u32 %0, 1, 0, p;\n\t}"
            : "=r"(ok) : "r"(bar), "r"(parity) : "memory");
        if (++it > kSpinLimit) __trap();
    } while (!ok);
}
__device__ __forceinline__ bool mbar_try(uint32_t bar, uint32_t parity) {
    uint32_t ok;
    asm volatile(
        "{\n\t.reg .pred p;\n\t"
        "mbarrier.try_wait.parity.shared::cta.b64 p, [%1], %2;\n\t"
        "selp.u32 %0, 1, 0, p;\n\t}"
        : "=r"(ok) : "r"(bar), "r"(parity) : "memory");
    return __all_sync(0xffffffffu, ok);
}
__device__ __forceinline__ void mbar_wait_u(uint32_t bar, uint32_t parity) {
    for (uint32_t it = 0; !mbar_try(bar, parity); it++)
        if (it > kSpinLimit) __trap();
}
__device__ __forceinline__ void prefetch_l2(const void* p) {
    asm volatile("prefetch.global.L2 [%0];" ::"l"(p) : "memory");
}
__device__ __forceinline__ void tma3d(uint32_t dst, const CUtensorMap* tm, int c0, int c1, int c2, uint32_t bar, uint64_t pol) {
    asm volatile(
        "cp.async.bulk.tensor.3d.shared::cluster.global.mbarrier::complete_tx::bytes.L2::cache_hint "
        "[%0], [%1, {%2, %3, %4}], [%5], %6;"
        ::"r"(dst), "l"(tm), "r"(c0), "r"(c1), "r"(c2), "r"(bar), "l"(pol) : "memory");
}
__device__ __forceinline__ void tma3d_prefetch(const CUtensorMap* tm, int c0, int c1, int c2, uint64_t pol) {
    asm volatile("cp.async.bulk.prefetch.tensor.3d.L2.global.L2::cache_hint [%0, {%1, %2, %3}], %4;"
                 ::"l"(tm), "r"(c0), "r"(c1), "r"(c2), "l"(pol) : "memory");
}
__device__ __forceinline__ uint64_t make_policy(bool keep) {
    uint64_t pol;
    if (keep) asm volatile("createpolicy.fractional.L2::evict_normal.b64 %0, 1.0;" : "=l"(pol));
    else      asm volatile("createpolicy.fractional.L2::evict_first.b64 %0, 1.0;" : "=l"(pol));
    return pol;
}
__device__ __forceinline__ void ldsm4(uint32_t (&r)[4], uint32_t addr) {
    asm volatile("ldmatrix.sync.aligned.m8n8.x4.shared.b16 {%0,%1,%2,%3}, [%4];"
                 : "=r"(r[0]), "=r"(r[1]), "=r"(r[2]), "=r"(r[3]) : "r"(addr) : "memory");
}
__device__ __forceinline__ void ldsm4t(uint32_t (&r)[4], uint32_t addr) {
    asm volatile("ldmatrix.sync.aligned.m8n8.x4.trans.shared.b16 {%0,%1,%2,%3}, [%4];"
                 : "=r"(r[0]), "=r"(r[1]), "=r"(r[2]), "=r"(r[3]) : "r"(addr) : "memory");
}
__device__ __forceinline__ void mma16816(float (&c)[4], const uint32_t (&a)[4], uint32_t b0, uint32_t b1) {
    asm volatile("mma.sync.aligned.m16n8k16.row.col.f32.bf16.bf16.f32 {%0,%1,%2,%3}, {%4,%5,%6,%7}, {%8,%9}, {%0,%1,%2,%3};"
                 : "+f"(c[0]), "+f"(c[1]), "+f"(c[2]), "+f"(c[3])
                 : "r"(a[0]), "r"(a[1]), "r"(a[2]), "r"(a[3]), "r"(b0), "r"(b1));
}
__device__ __forceinline__ float bf16r(float v) { return __bfloat162float(__float2bfloat16_rn(v)); }
__device__ __forceinline__ uint32_t pack_bf16(float lo, float hi) {
    uint32_t r;
    asm("cvt.rn.bf16x2.f32 %0, %1, %2;" : "=r"(r) : "f"(hi), "f"(lo));
    return r;
}
__device__ __forceinline__ bool elect() {
    uint32_t p;
    asm volatile("{\n\t.reg .pred e;\n\telect.sync _|e, 0xffffffff;\n\tselp.u32 %0, 1, 0, e;\n\t}" : "=r"(p));
    return p;
}
__device__ __forceinline__ float fast_sqrt(float v) {
    float r;
    asm("sqrt.approx.f32 %0, %1;" : "=f"(r) : "f"(v));
    return r;
}
__device__ __forceinline__ float ex2(float v) {
    float r;
    asm("ex2.approx.ftz.f32 %0, %1;" : "=f"(r) : "f"(v));
    return r;
}
__device__ __forceinline__ void st_packet(uint4* p, uint32_t a, uint32_t b, uint32_t c, uint32_t tag) {
    asm volatile(
        "{\n\t.reg .b64 lo, hi;\n\t.reg .b128 v;\n\t"
        "mov.b64 lo, {%1, %2};\n\tmov.b64 hi, {%3, %4};\n\tmov.b128 v, {lo, hi};\n\t"
        "st.relaxed.gpu.global.b128 [%0], v;\n\t}"
        ::"l"(p), "r"(a), "r"(b), "r"(c), "r"(tag) : "memory");
}
__device__ __forceinline__ void st_packet(uint4* p, float a, float b, float c, uint32_t tag) {
    st_packet(p, __float_as_uint(a), __float_as_uint(b), __float_as_uint(c), tag);
}
__device__ __forceinline__ uint4 ld_packet(const uint4* p) {
    uint4 v;
    asm volatile(
        "{\n\t.reg .b64 lo, hi;\n\t.reg .b128 v;\n\t"
        "ld.relaxed.gpu.global.b128 v, [%4];\n\t"
        "mov.b128 {lo, hi}, v;\n\tmov.b64 {%0, %1}, lo;\n\tmov.b64 {%2, %3}, hi;\n\t}"
        : "=r"(v.x), "=r"(v.y), "=r"(v.z), "=r"(v.w) : "l"(p) : "memory");
    return v;
}
__device__ __forceinline__ void red_packet(float4* p, float a, float b, float c) {
    asm volatile("red.relaxed.gpu.global.add.v4.f32 [%0], {%1, %2, %3, %4};"
                 ::"l"(p), "f"(a), "f"(b), "f"(c), "f"(1.f) : "memory");
}
#define POLL_UNTIL(loads, done)                 \
    for (uint32_t it_ = 0;; it_++) {            \
        loads;                                  \
        if (__all_sync(0xffffffffu, done)) break; \
        if (it_ > kSpinLimit) __trap();         \
        POLL_SLEEP;                             \
    }
__device__ __forceinline__ uint32_t round24(float v) {
    const uint32_t u = __float_as_uint(v);
    return u + ((u & 0x7f800000u) == 0x7f800000u ? 0u : 0x80u);
}
__device__ __forceinline__ void st_packet5(uint4* p, const float* v, uint32_t tag) {
    const uint32_t r0 = round24(v[0]), r1 = round24(v[1]), r2 = round24(v[2]), r3 = round24(v[3]), r4 = round24(v[4]);
    st_packet(p, __byte_perm(r0, r1, 0x5321), __byte_perm(r1, r2, 0x6532), __byte_perm(r2, r3, 0x7653),
              (r4 >> 8) | (tag << 24));
}
__device__ __forceinline__ void add_packet5(float (&a)[5], const uint4& v) {
    a[0] += __uint_as_float(v.x << 8);
    a[1] += __uint_as_float(__funnelshift_r(v.x, v.y, 16) & 0xffffff00u);
    a[2] += __uint_as_float(__funnelshift_r(v.y, v.z, 8) & 0xffffff00u);
    a[3] += __uint_as_float(v.z & 0xffffff00u);
    a[4] += __uint_as_float(v.w << 8);
}
__device__ __forceinline__ uint32_t now_ns() {
    uint32_t t;
    asm volatile("mov.u32 %0, %globaltimer_lo;" : "=r"(t));
    return t;
}
__device__ __forceinline__ float bf_lo(uint32_t v) { return __uint_as_float(v << 16); }
__device__ __forceinline__ float bf_hi(uint32_t v) { return __uint_as_float(v & 0xffff0000u); }
__device__ __forceinline__ float warp_sum(float v) {
#pragma unroll
    for (int o = 16; o > 0; o >>= 1) v += __shfl_xor_sync(0xffffffffu, v, o);
    return v;
}

constexpr float kLog2e = 1.4426950408889634f;
constexpr float kScale = 0.07216878364870322f;

struct Attn {
    float m, l;
    float acc[3][4];
};

__device__ __forceinline__ float score(float dot) { return bf16r(bf16r(dot) * kScale); }

__device__ __forceinline__ uint32_t probability(Attn& st, float s) {
    const float e = ex2((s - st.m) * kLog2e);
    st.l += e;
    const float hi = bf16r(e);
    const uint32_t hl = pack_bf16(hi, e - hi);
    uint32_t pv;
    asm volatile("movmatrix.sync.aligned.m8n8.trans.b16 %0, %1;" : "=r"(pv) : "r"(hl));
    return pv;
}

__device__ __forceinline__ uint32_t softmax_step(Attn& st, float dot) {
    const float s = score(dot);
    if (__any_sync(0xffffffffu, s > st.m)) {
        float mx = fmaxf(s, __shfl_xor_sync(0xffffffffu, s, 4));
        mx = fmaxf(mx, __shfl_xor_sync(0xffffffffu, mx, 8));
        mx = fmaxf(mx, __shfl_xor_sync(0xffffffffu, mx, 16));
        mx = fmaxf(mx, st.m);
        const float corr = ex2((st.m - mx) * kLog2e);
        st.m = mx;
        st.l *= corr;
#pragma unroll
        for (int a = 0; a < 3; a++)
#pragma unroll
            for (int i = 0; i < 4; i++) st.acc[a][i] *= corr;
    }
    return probability(st, s);
}

#define TRACE_G(i)
#define TRACE_C(i)

__global__ void __launch_bounds__(kThreads, 1)
fused_decode_kernel(const __grid_constant__ Params P) {
    extern __shared__ __align__(1024) unsigned char smem[];
    const uint32_t sbase = (uint32_t)__cvta_generic_to_shared(smem);
    const uint32_t sync0 = sbase + kOffSync;
    float* const wbuf = reinterpret_cast<float*>(smem + kOffWbuf);

    const int lane = threadIdx.x & 31;
    const int w = __shfl_sync(0xffffffffu, threadIdx.x >> 5, 0);
    const int cta = blockIdx.x;
    const int h = cta >> 2, jq = cta & 3;

    if (elect()) {
        if (w == 8) {
#pragma unroll
            for (int i = 0; i < kSlots; i++) mbar_init(sbase + kOffFull + 8 * i, 1);
            asm volatile("fence.mbarrier_init.release.cluster;" ::: "memory");
#pragma unroll
            for (int p = 0; p < kRing; p++) {
                mbar_expect(sbase + kOffFull + 8 * p, 8 * kSlotBytes);
                tma3d(sbase + p * 8 * kSlotBytes, &P.tm[4], 0, 160 * jq + (p == 2 ? 96 : 64 * p), 3 * h,
                      sbase + kOffFull + 8 * p, make_policy(false));
                if (P.loads[0] & LD_KEEP) tma3d_prefetch(&P.tm[4], 0, 160 * jq + (p == 2 ? 96 : 64 * p), 3 * h, make_policy(true));
            }
#pragma unroll
            for (int i = 0; i < kSlots; i++) mbar_init(sbase + kOffEmpty + 8 * i, 8);
        } else if (w == 9) {
#pragma unroll
            for (int i = 0; i < 8; i++) asm volatile("prefetch.tensormap [%0];" ::"l"(&P.tm[i]) : "memory");
        } else if (w == 10) {
#pragma unroll
            for (int i = 0; i < 14; i++) mbar_init(sync0 + 8 * i, (8 * i == kBarRows || 8 * i >= kBarSentY) ? 8 : 1);
        }
        if (w != 9) asm volatile("fence.mbarrier_init.release.cluster;" ::: "memory");
    }
    __syncwarp();
    if (w == 8) asm volatile("bar.arrive 1, %0;" ::"n"(kThreads) : "memory");
    else asm volatile("bar.sync 1, %0;" ::"n"(kThreads) : "memory");

    if (w < 8) {
        asm volatile("setmaxnreg.inc.sync.aligned.u32 232;");
        const uint32_t full0 = sbase + kOffFull;
        const uint32_t frag0 = sbase + w * 1024 + (lane & 7) * 128 + (((lane >> 3) ^ (lane & 7)) << 4), frag1 = frag0 ^ 64;
        auto frag_addr = [&](uint32_t s, int k) { return ((k & 1) ? frag1 : frag0) + s * (8 * kSlotBytes) + (k >> 1) * 8192; };
        uint32_t par = 0, rpos = 0, nrows = 0;
        auto wait_tile = [&](uint32_t s) { mbar_wait(full0 + 8 * s, (par >> s) & 1u); };
        auto tile_ready = [&](uint32_t s) { return mbar_test(full0 + 8 * s, (par >> s) & 1u); };
        auto release = [&](uint32_t s) {
            par ^= 1u << s;
            __syncwarp();
            if (elect()) mbar_arrive(full0 + 8 * s + (kOffEmpty - kOffFull));
        };
        auto ring_release = [&]() {
            release(rpos);
            if (++rpos == kRing) rpos = 0;
        };
        auto row_acquire = [&]() { mbar_wait(sync0 + kBarFree, (nrows & 1) ^ 1); };
        auto row_publish = [&]() {
            __syncwarp();
            if (elect()) mbar_arrive(sync0 + kBarRows);
            nrows++;
        };

        uint32_t rf[8][6][4];
#pragma unroll
        for (int i = 0; i < 8; i++)
#pragma unroll
            for (int s = 0; s < 6; s++)
#pragma unroll
                for (int k = 0; k < 4; k++) rf[i][s][k] = 0;

#pragma unroll 1
        for (int pc = 0;; pc++) {
            const uint32_t op = P.prog[pc];
            const uint32_t kind = op & 7u;
            if (kind == OP_END) break;
            int lane = threadIdx.x & 31;
            asm volatile("" : "+r"(lane));
            const int g = lane >> 2, t = lane & 3;
            float* const row = wbuf + w * kWRow;

            if (kind == OP_SEG) {
                const uint32_t b = (op >> 3) & 1u;
                mbar_wait(sync0 + kBarQ + 8 * b, (op >> 4) & 1u);
                const uint2* qf = reinterpret_cast<const uint2*>(smem + kOffQf) + b * 48 + (lane & 7);
                Attn st;
                st.m = -INFINITY; st.l = 0.f;
#pragma unroll
                for (int a = 0; a < 3; a++)
#pragma unroll
                    for (int i = 0; i < 4; i++) st.acc[a][i] = 0.f;

                if (op & (1u << 7)) {
                    float c[4][4] = {};
#pragma unroll
                    for (int k = 0; k < 6; k++) {
                        const uint2 q = qf[8 * k];
#pragma unroll
                        for (int i = 0; i < 4; i++) mma16816(c[i], rf[2 * i][k], q.x, q.y);
                    }
                    float sc[4];
#pragma unroll
                    for (int i = 0; i < 4; i++) sc[i] = score(c[i][0] + c[i][3]);
                    float mx = fmaxf(fmaxf(sc[0], sc[1]), fmaxf(sc[2], sc[3]));
                    mx = fmaxf(mx, __shfl_xor_sync(0xffffffffu, mx, 4));
                    mx = fmaxf(mx, __shfl_xor_sync(0xffffffffu, mx, 8));
                    st.m = fmaxf(mx, __shfl_xor_sync(0xffffffffu, mx, 16));
                    uint32_t pv[4];
#pragma unroll
                    for (int i = 0; i < 4; i++) pv[i] = probability(st, sc[i]);
#pragma unroll
                    for (int i = 0; i < 4; i++)
#pragma unroll
                        for (int k = 0; k < 6; k++)
                            mma16816(st.acc[k >> 1], rf[2 * i + 1][k], (g >> 1) == 2 * (k & 1) ? pv[i] : 0u,
                                     (g >> 1) == 2 * (k & 1) + 1 ? pv[i] : 0u);
                }

                uint32_t lo = P.prog[pc + 1], hi = P.prog[pc + 2];
                pc += 2;
                bool haveK = false;
#pragma unroll 1
                while (lo & 15u) {
                    const bool rel = lo & 4u;
                    uint32_t sK = kRing - 2 + 2 * (lo & 3u), sV = sK + 1;
                    if (!(lo & 3u)) {
                        sK = rpos;
                        sV = rpos == kRing - 1 ? 0 : rpos + 1;
                        rpos = sV == kRing - 1 ? 0 : sV + 1;
                    }
                    lo = __funnelshift_r(lo, hi, 4);
                    hi >>= 4;
                    if (!haveK) wait_tile(sK);
                    const bool haveV = tile_ready(sV);
                    float c[2][4] = {};
#pragma unroll
                    for (int k = 0; k < 6; k++) {
                        uint32_t a[4];
                        ldsm4(a, frag_addr(sK, k));
                        const uint2 q = qf[8 * k];
                        mma16816(c[k & 1], a, q.x, q.y);
                    }
                    if (rel) release(sK);
                    const uint32_t pv = softmax_step(st, (c[0][0] + c[0][3]) + (c[1][0] + c[1][3]));
                    if (!haveV) wait_tile(sV);
                    haveK = tile_ready((lo & 3u) ? kRing - 2 + 2 * (lo & 3u) : rpos);
#pragma unroll
                    for (int k = 0; k < 6; k++) {
                        uint32_t a[4];
                        ldsm4t(a, frag_addr(sV, k));
                        mma16816(st.acc[k >> 1], a, (g >> 1) == 2 * (k & 1) ? pv : 0u, (g >> 1) == 2 * (k & 1) + 1 ? pv : 0u);
                    }
                    if (rel) release(sV);
                }

                TRACE_C(4);
                float l = st.l;
                l += __shfl_xor_sync(0xffffffffu, l, 4);
                l += __shfl_xor_sync(0xffffffffu, l, 8);
                l += __shfl_xor_sync(0xffffffffu, l, 16);
                row_acquire();
#pragma unroll
                for (int a = 0; a < 3; a++) {
                    row[64 * a + 16 * t + g] = st.acc[a][0] + st.acc[a][1];
                    row[64 * a + 16 * t + g + 8] = st.acc[a][2] + st.acc[a][3];
                }
                if (lane == 0) { row[192] = st.m; row[193] = l; }
                row_publish();
            } else if (kind == OP_RFLOAD) {
#pragma unroll 1
                for (uint32_t tile = (op >> 2) & 6u; tile <= ((op >> 2) | 1u); tile++) {
                    wait_tile(rpos);
#pragma unroll
                    for (int i = 0; i < 8; i++) {
                        if (tile == i) {
#pragma unroll
                            for (int k = 0; k < 6; k++) {
                                if (i & 1) ldsm4t(rf[i][k], frag_addr(rpos, k));
                                else ldsm4(rf[i][k], frag_addr(rpos, k));
                            }
                        }
                    }
                    ring_release();
                }
            } else if (kind == OP_QPROJ) {
                const uint32_t mask = (op >> 3) & 3u;
#pragma unroll 1
                for (uint32_t b = 0; b < 2; b++)
                    if ((mask >> b) & 1u) mbar_wait(sync0 + kBarXn + 8 * b, (op >> 5) & 1u);
                const uint32_t bb = mask == 3u ? (g & 1) : (mask >> 1);
                const uint32_t* xs = reinterpret_cast<const uint32_t*>(smem + kOffXn) + bb * 80 + 4 * w + t;
                float acc[3][4] = {};
#pragma unroll 1
                for (int p = 0; p < 3; p++) {
                    uint32_t xv = xs[p == 2 ? 48 : 32 * p];
                    if (p == 2 && w < 4) xv = 0u;
                    wait_tile(rpos);
#pragma unroll
                    for (int k = 0; k < 6; k++) {
                        uint32_t a[4];
                        ldsm4t(a, frag_addr(rpos, k));
                        mma16816(acc[k >> 1], a, (g >> 1) == 2 * (k & 1) ? xv : 0u, (g >> 1) == 2 * (k & 1) + 1 ? xv : 0u);
                    }
                    ring_release();
                }
#pragma unroll 1
                for (uint32_t b = 0; b < 2; b++) {
                    if (!((mask >> b) & 1u)) continue;
                    row_acquire();
#pragma unroll
                    for (int a = 0; a < 3; a++) {
                        row[64 * a + 16 * t + g] = b ? acc[a][1] : acc[a][0];
                        row[64 * a + 16 * t + g + 8] = b ? acc[a][3] : acc[a][2];
                    }
                    row_publish();
                }
            } else {
                const uint32_t mask = (op >> 3) & 3u;
                const uint32_t bb = mask == 3u ? (g & 1) : (mask >> 1);
                const uint32_t* ob = reinterpret_cast<const uint32_t*>(smem + kOffObf) + bb * 24 + t;
                const uint32_t roff = ((lane & 7) + 8 * (lane >> 4)) * 128 + ((((lane >> 3) & 1) ^ (lane & 7)) << 4);
                const bool ring = !(op >> 8);
                uint32_t sl[3];
#pragma unroll
                for (int p = 0; p < 3; p++) {
                    sl[p] = ring ? rpos : (op >> 8) + p;
                    if (ring && ++rpos == kRing) rpos = 0;
                }
                auto frag = [&](uint32_t (&a)[4], int p, int mt) {
                    ldsm4t(a, ((sbase + sl[p] * 8 * kSlotBytes + roff) ^ (((5 * w + mt) & 3) << 5)) + ((5 * w + mt) >> 2) * 2048);
                };
                uint32_t a0[5][4];
                wait_tile(sl[0]);
#pragma unroll
                for (int mt = 0; mt < 5; mt++) frag(a0[mt], 0, mt);
                if (ring) release(sl[0]);
                wait_tile(sl[1]);
                wait_tile(sl[2]);
                if (mask & 1u) mbar_wait(sync0 + kBarO, (op >> 5) & 1u);
                if (mask & 2u) mbar_wait(sync0 + kBarO + 8, (op >> 5) & 1u);
                TRACE_C(0);
                float c[3][4] = {};
#pragma unroll
                for (int p = 0; p < 3; p++) {
                    const uint32_t b0 = ob[8 * p], b1 = ob[8 * p + 4];
#pragma unroll
                    for (int mt = 0; mt < 5; mt++) {
                        if (p > 0) frag(a0[mt], p, mt);
                        const bool on = (g >> 1) == (mt & 3);
                        mma16816(c[mt == 4 ? 2 : (mt & 1)], a0[mt], on ? b0 : 0u, on ? b1 : 0u);
                    }
                    if (p > 0 && ring) release(sl[p]);
                }
                TRACE_C(1);
                row_acquire();
                TRACE_C(2);
                row[16 * t + g] = c[0][0] + c[1][0]; row[80 + 16 * t + g] = c[0][1] + c[1][1];
                row[16 * t + g + 8] = c[0][2] + c[1][2]; row[80 + 16 * t + g + 8] = c[0][3] + c[1][3];
                if (t == 0) {
                    row[64 + g] = c[2][0]; row[144 + g] = c[2][1];
                    row[72 + g] = c[2][2]; row[152 + g] = c[2][3];
                }
                __syncwarp();
#pragma unroll 1
                for (uint32_t b = 0; b < 2; b++)
                    if (((mask >> b) & 1u) && lane < 27) {
                        const float* y = row + 80 * b + 3 * lane;
                        float4* dst = ((op >> 5) & 3u) == 3u ? g_out[b][cta % kOutReplicas] : g_acc[b][(op >> 5) & 3u];
                        red_packet(dst + 27 * w + lane, y[0], y[1], lane < 26 ? y[2] : 0.f);
                    }
                TRACE_C(3);
                __syncwarp();
                if (lane < 2 && ((mask >> lane) & 1u)) mbar_arrive(sync0 + kBarSentY + 8 * lane);
            }
        }
    } else {
        asm volatile("setmaxnreg.dec.sync.aligned.u32 40;");
        if (w == 8) {
            const int rowA = h * 4096 + 3072 + 256 * jq, rowB = h * 4096 + 1024 * jq;
            const int rowWq = 160 * jq, rowWo = 192 * h + 48 * jq;
            const uint32_t tau = P.tau, tauLow = P.tauLow, tauW = P.tauW, credit = P.credit;
            const uint32_t winLow = P.winLow, winHigh = P.winHigh;
            const uint64_t polKeep = make_policy(true), polStream = make_policy(false);
            uint32_t fifo = 0x012u, queued = 7u, stale = 0, par = 7u, nfl = kRing, next = now_ns() + P.startDelay;
            auto coord = [&](uint32_t e) {
                return (int)((e >> 10) & 0x7ffffu) + ((e & 4u) ? ((e & 2u) ? rowWo : rowWq) : ((e & 2u) ? rowB : rowA));
            };
            auto interval = [&](uint32_t e) { return (e & 4u) ? tauW : ((e & LD_LOW) ? tauLow : tau); };
            uint32_t recent = 0x012u;
            auto slot_free = [&](uint32_t s) { return mbar_test(sbase + kOffEmpty + 8 * s, ((par >> s) & 1u) ^ 1u); };
            auto landed = [&](uint32_t s) { return mbar_test(sbase + kOffFull + 8 * s, ((par >> s) & 1u) ^ 1u); };
            auto load = [&](uint32_t e, bool counted) {
                const uint32_t s = (e >> 4) & 15u;
                const int c1 = coord(e), c2 = ((e >> 1) & 3u) == 2u ? 3 * h : 0;
                if (elect()) {
                    mbar_expect(sbase + kOffFull + 8 * s, (e & 6u) == 6u ? 20480 : 8 * kSlotBytes);
                    const bool again = (e & (LD_KEEP | LD_HIT)) == (LD_KEEP | LD_HIT);
                    tma3d(sbase + s * 8 * kSlotBytes, &P.tm[e & 7u], 0, c1, c2, sbase + kOffFull + 8 * s, again ? polKeep : polStream);
                    if ((e & LD_KEEP) && !again) tma3d_prefetch(&P.tm[e & 7u], 0, c1, c2, polKeep);
                }
                if (counted) {
                    fifo = (fifo << 4) | s;
                    queued |= 1u << s;
                    nfl++;
                    recent = (recent << 4) | s;
                }
                par ^= 1u << s;
            };
            uint32_t m = 0, pfd = 0;
#pragma unroll 1
            for (uint32_t n = kRing;; n++) {
                const uint32_t e = P.loads[n];
                if (!(e & LD_VALID)) break;
                const uint32_t s = (e >> 4) & 15u;
                if (m < n) m = n;
                const uint32_t look = (e & LD_FAR) ? P.lookFar : P.look;
                for (uint32_t it = 0; !slot_free(s); it++) {
                    if (it > 16 * kSpinLimit) __trap();
                    const uint32_t f = P.loads[m];
                    if (m >= n + look || !(f & LD_VALID)) continue;
                    if (f & LD_HIT) {
                        if (P.hitTouch && m > n && elect()) tma3d_prefetch(&P.tm[f & 7u], 0, coord(f), 0, polKeep);
                        m++;
                        continue;
                    }
                    const uint32_t now = now_ns();
                    if ((int)(now - next) >= 0 && landed((recent >> (4 * P.lookBack)) & 15u)) {
                        if (elect()) tma3d_prefetch(&P.tm[f & 7u], 0, coord(f), ((f >> 1) & 3u) == 2u ? 3 * h : 0, polStream);
                        next = now + interval(f);
                        pfd |= 1u << (m & 31u);
                        m++;
                    }
                }
                stale |= queued & (1u << s);
                queued &= ~(1u << s);
                const bool counted = !(e & LD_HIT) && !((pfd >> (n & 31u)) & 1u);
                pfd &= ~(1u << (n & 31u));
                if (counted) {
                    for (const uint32_t win = n < P.nStart ? P.winStart : ((e & LD_LOW) ? winLow : winHigh); nfl >= win; nfl--) {
                        const uint32_t o = (fifo >> (4 * nfl - 4)) & 15u;
                        if ((stale >> o) & 1u) {
                            stale ^= 1u << o;
                        } else {
                            mbar_wait_u(sbase + kOffFull + 8 * o, ((par >> o) & 1u) ^ 1u);
                            queued ^= 1u << o;
                        }
                    }
                    if (e & LD_ANCHOR)
                        next = __shfl_sync(0xffffffffu, *reinterpret_cast<volatile uint32_t*>(smem + kOffAnchor), 0) + P.anchorDelay;
                    uint32_t now = now_ns();
                    while ((int)(now - next) < 0) now = now_ns();
                    if ((int)(now - credit - next) > 0) next = now - credit;
                    next += interval(e);
                }
                load(e, counted);
            }
        } else {
            if (w == 9) {
#pragma unroll 1
                for (int n = 0;; n++) {
                    const uint32_t job = P.merge[n];
                    if ((job & 3u) == MG_END) break;
                    const uint32_t b = (job >> 2) & 1u;
                    const uint32_t tag = 1 + ((job >> 3) & 3u);
                    mbar_wait(sync0 + kBarRows, n & 1);
                    if ((job & 3u) == MG_Q) {
#pragma unroll 1
                        for (int u = lane; u < 40; u += 32) {
                            float o[5] = {};
#pragma unroll
                            for (int i = 0; i < 8; i++)
#pragma unroll
                                for (int k = 0; k < 5; k++) o[k] += wbuf[i * kWRow + 5 * min(u, 38) + k];
                            st_packet5(&g_q[b][h][jq][u], o, tag);
                        }
                        __syncwarp();
                        if (lane == 0) mbar_arrive(sync0 + kBarSentQ + 8 * b);
                    } else {
                        float* cp = reinterpret_cast<float*>(smem + kOffCpart) + b * kWRow;
                        const bool merge = !(job & 32u);
                        float mi = -INFINITY, li = 0.f;
                        if (lane < 8) { mi = wbuf[lane * kWRow + 192]; li = wbuf[lane * kWRow + 193]; }
                        else if (lane == 8 && merge) { mi = cp[192]; li = cp[193]; }
                        float M = mi;
#pragma unroll
                        for (int o = 8; o > 0; o >>= 1) M = fmaxf(M, __shfl_xor_sync(0xffffffffu, M, o));
                        M = __shfl_sync(0xffffffffu, M, 0);
                        const float sc = ex2((mi - M) * kLog2e);
                        const float L = warp_sum(li * sc);
                        const float ps = __shfl_sync(0xffffffffu, sc, 8);
                        float o[2][3];
#pragma unroll
                        for (int r = 0; r < 2; r++)
#pragma unroll
                            for (int k = 0; k < 3; k++) o[r][k] = merge ? cp[3 * (lane + 32 * r) + k] * ps : 0.f;
#pragma unroll
                        for (int i = 0; i < 8; i++) {
                            const float si = __shfl_sync(0xffffffffu, sc, i);
#pragma unroll
                            for (int r = 0; r < 2; r++)
#pragma unroll
                                for (int k = 0; k < 3; k++)
                                    o[r][k] = fmaf(wbuf[i * kWRow + 3 * (lane + 32 * r) + k], si, o[r][k]);
                        }
                        if (job & 64u) {
#pragma unroll
                            for (int r = 0; r < 2; r++)
                                st_packet(&g_p[b][h][(lane >> 4) + 2 * r][jq][lane & 15], o[r][0], o[r][1], o[r][2], tag);
                            if (lane < 8) st_packet(&g_p[b][h][lane >> 1][jq][16 + (lane & 1)], M, L, 0.f, tag);
                            if (lane == 0) mbar_arrive(sync0 + kBarSentP + 8 * b);
                        } else {
#pragma unroll
                            for (int r = 0; r < 2; r++)
#pragma unroll
                                for (int k = 0; k < 3; k++) cp[3 * (lane + 32 * r) + k] = o[r][k];
                            if (lane == 0) { cp[192] = M; cp[193] = L; }
                        }
                    }
                    __syncwarp();
                    if (lane == 0) mbar_arrive(sync0 + kBarFree);
                }
            } else {
                const uint32_t b = w - 10;
                __nv_bfloat16* const xn = reinterpret_cast<__nv_bfloat16*>(smem + kOffXn) + b * 160;
                __nv_bfloat16* const qd = reinterpret_cast<__nv_bfloat16*>(smem + kOffQf) + b * 192;
                __nv_bfloat16* const ob = reinterpret_cast<__nv_bfloat16*>(smem + kOffObf) + b * 48;
#pragma unroll 1
                for (uint32_t layer = 0; layer < 4; layer++) {
                    const uint32_t tag = layer + 1;
                    int lane = threadIdx.x & 31;
                    asm volatile("" : "+r"(lane));
                    {
                        uint32_t x01[7], x2[7];
                        if (layer == 0) {
#pragma unroll
                            for (int i = 0; i < 7; i++) {
                                const int p = lane + 32 * i, u = p % 27;
                                const unsigned short* xp = reinterpret_cast<const unsigned short*>(P.x) + b * 640 + (p / 27) * 80 + 3 * u;
                                x01[i] = p < kAccPackets ? xp[0] | ((uint32_t)xp[1] << 16) : 0u;
                                x2[i] = (p < kAccPackets && u < 26) ? xp[2] : 0u;
                            }
                        } else {
                            mbar_wait(sync0 + kBarSentY + 8 * b, (layer - 1) & 1);
                            TRACE_G(4 * layer - 1);
                            uint4 v[7];
                            const uint4* src = reinterpret_cast<const uint4*>(&g_acc[b][layer - 1][lane]);
                            const uint32_t done = __float_as_uint(kAccDone);
                            POLL_UNTIL(v[0] = ld_packet(src - lane + 27 * (cta & 7) + min(lane, 26)), v[0].w == done);
                            POLL_UNTIL(
                                v[0] = ld_packet(src); v[1] = ld_packet(src + 32); v[2] = ld_packet(src + 64);
                                v[3] = ld_packet(src + 96); v[4] = ld_packet(src + 128); v[5] = ld_packet(src + 160);
                                v[6] = ld_packet(src + (lane < 24 ? 192 : 0)),
                                v[0].w == done && v[1].w == done && v[2].w == done && v[3].w == done && v[4].w == done &&
                                    v[5].w == done && v[6].w == done);
#pragma unroll
                            for (int i = 0; i < 7; i++) {
                                x01[i] = pack_bf16(__uint_as_float(v[i].x), __uint_as_float(v[i].y));
                                x2[i] = pack_bf16(__uint_as_float(v[i].z), 0.f);
                            }
                            if (lane >= 24) x01[6] = x2[6] = 0u;
                        }
                        TRACE_G(16 + 4 * layer);
                        float sum = 0.f;
#pragma unroll
                        for (int i = 0; i < 7; i++) sum += (bf_lo(x01[i]) + bf_hi(x01[i])) + bf_lo(x2[i]);
                        const float mean = warp_sum(sum) * (1.f / 640.f);
                        float sq = 0.f;
#pragma unroll
                        for (int i = 0; i < 7; i++) {
                            const bool none = i == 6 && lane >= 24;
                            const float d0 = none ? 0.f : bf_lo(x01[i]) - mean, d1 = none ? 0.f : bf_hi(x01[i]) - mean;
                            const bool last = lane == 26 - 5 * i || lane == 53 - 5 * i;
                            const float d2 = (none || last) ? 0.f : bf_lo(x2[i]) - mean;
                            sq += fmaf(d0, d0, fmaf(d1, d1, d2 * d2));
                        }
                        const float var = warp_sum(sq) * (1.f / 640.f);
                        const float meanb = bf16r(mean);
                        const float rden = __fdividef(1.f, bf16r(fast_sqrt(bf16r(bf16r(var) + 1e-5f))));
#pragma unroll
                        for (int i = 0; i < 7; i++) {
                            const uint32_t q = lane + 32 * i - 54 * jq;
                            if (q < 54u) {
                                const int c = 3 * q - (q >= 27u);
                                xn[c] = __float2bfloat16_rn(bf16r(bf_lo(x01[i]) - meanb) * rden);
                                xn[c + 1] = __float2bfloat16_rn(bf16r(bf_hi(x01[i]) - meanb) * rden);
                                if (q != 26u && q != 53u) xn[c + 2] = __float2bfloat16_rn(bf16r(bf_lo(x2[i]) - meanb) * rden);
                            }
                        }
                        if (lane == 0) *reinterpret_cast<volatile uint32_t*>(smem + kOffAnchor) = now_ns();
                        __syncwarp();
                        if (lane == 0) mbar_arrive(sync0 + kBarXn + 8 * b);
                        TRACE_G(4 * layer);
#pragma unroll
                        for (int i = 0; i < 7; i++) {
                            const int p = lane + 32 * i;
                            if ((p & 127) == cta && p < kAccPackets) {
                                red_packet((layer == 3 ? g_out[b][0] : g_acc[b][layer]) + p, bf_lo(x01[i]), bf_hi(x01[i]), bf_lo(x2[i]));
                                if (layer >= 2) g_acc[b][layer - 2][p] = make_float4(0.f, 0.f, 0.f, 0.f);
                            }
                        }
                    }
                    {
                        mbar_wait(sync0 + kBarSentQ + 8 * b, layer & 1);
                        uint4 v[5];
                        const uint4* src = &g_q[b][h][0][lane];
                        const uint4* ext = &g_q[b][h][lane & 3][lane < 28 ? 32 + (lane >> 2) : 38];
                        POLL_UNTIL(
                            v[0] = ld_packet(src); v[1] = ld_packet(src + 40); v[2] = ld_packet(src + 80);
                            v[3] = ld_packet(src + 120); v[4] = ld_packet(ext),
                            (v[0].w >> 24) == tag && (v[1].w >> 24) == tag && (v[2].w >> 24) == tag &&
                                (v[3].w >> 24) == tag && (v[4].w >> 24) == tag);
                        __syncwarp();
                        TRACE_G(16 + 4 * layer + 1);
                        auto store_q = [&](int d, float q) {
                            qd[(d & ~31) + ((d >> 3) & 1) * 16 + ((d >> 1) & 3) * 4 + ((d >> 4) & 1) * 2 + (d & 1)] =
                                __float2bfloat16_rn(q);
                        };
                        float a[5] = {};
#pragma unroll
                        for (int i = 0; i < 4; i++) add_packet5(a, v[i]);
#pragma unroll
                        for (int k = 0; k < 5; k++) store_q(5 * lane + k, a[k]);
                        float e[5] = {};
                        add_packet5(e, v[4]);
#pragma unroll
                        for (int k = 0; k < 5; k++) {
                            e[k] += __shfl_xor_sync(0xffffffffu, e[k], 1);
                            e[k] += __shfl_xor_sync(0xffffffffu, e[k], 2);
                            const int d = 160 + 5 * (lane >> 2) + k;
                            if ((lane & 3) == 0 && d < 192) store_q(d, e[k]);
                        }
                        __syncwarp();
                        if (lane == 0) mbar_arrive(sync0 + kBarQ + 8 * b);
                        TRACE_G(4 * layer + 1);
                    }
                    if (P.exp) break;
                    {
                        mbar_wait(sync0 + kBarSentP + 8 * b, layer & 1);
                        uint4 v0, v1, ml;
                        const uint4* src = &g_p[b][h][jq][2 * (lane >> 4)][lane & 15];
                        const uint4* mls = &g_p[b][h][jq][lane & 3][16];
                        POLL_UNTIL(v0 = ld_packet(src); v1 = ld_packet(src + 18); ml = ld_packet(mls),
                                   v0.w == tag && v1.w == tag && ml.w == tag);
                        __syncwarp();
                        TRACE_G(16 + 4 * layer + 2);
                        const float mi = __uint_as_float(ml.x);
                        float M = fmaxf(mi, __shfl_xor_sync(0xffffffffu, mi, 1));
                        M = fmaxf(M, __shfl_xor_sync(0xffffffffu, M, 2));
                        const float sc = ex2((mi - M) * kLog2e);
                        float L = __uint_as_float(ml.y) * sc;
                        L += __shfl_xor_sync(0xffffffffu, L, 1);
                        L += __shfl_xor_sync(0xffffffffu, L, 2);
                        const float s0 = __shfl_sync(0xffffffffu, sc, 2 * (lane >> 4));
                        const float s1 = __shfl_sync(0xffffffffu, sc, 2 * (lane >> 4) + 1);
                        float o0 = fmaf(__uint_as_float(v0.x), s0, __uint_as_float(v1.x) * s1);
                        float o1 = fmaf(__uint_as_float(v0.y), s0, __uint_as_float(v1.y) * s1);
                        float o2 = fmaf(__uint_as_float(v0.z), s0, __uint_as_float(v1.z) * s1);
                        o0 += __shfl_xor_sync(0xffffffffu, o0, 16);
                        o1 += __shfl_xor_sync(0xffffffffu, o1, 16);
                        o2 += __shfl_xor_sync(0xffffffffu, o2, 16);
                        if (lane < 16) {
                            ob[3 * lane] = __float2bfloat16_rn(__fdividef(o0, L));
                            ob[3 * lane + 1] = __float2bfloat16_rn(__fdividef(o1, L));
                            ob[3 * lane + 2] = __float2bfloat16_rn(__fdividef(o2, L));
                        }
                        __syncwarp();
                        if (lane == 0) mbar_arrive(sync0 + kBarO + 8 * b);
                        TRACE_G(4 * layer + 2);
                    }
                }
                if (!P.exp) {
                    mbar_wait(sync0 + kBarSentY + 8 * b, 1);
                    const int p = cta + 128 * ((lane >> 3) & 1), r = lane & 7;
                    float4* src = &g_out[b][r][p < kAccPackets ? p : cta];
                    const float want = kCtas / kOutReplicas + (r == 0);
                    uint4 v;
                    for (uint32_t it = 0;; it++) {
                        v = ld_packet(reinterpret_cast<const uint4*>(src));
                        if (__all_sync(0xffffffffu, v.w == __float_as_uint(want))) break;
                        if (it > kSpinLimit) __trap();
                    }
                    float o0 = __uint_as_float(v.x), o1 = __uint_as_float(v.y), o2 = __uint_as_float(v.z);
#pragma unroll
                    for (int o = 1; o < 8; o <<= 1) {
                        o0 += __shfl_xor_sync(0xffffffffu, o0, o);
                        o1 += __shfl_xor_sync(0xffffffffu, o1, o);
                        o2 += __shfl_xor_sync(0xffffffffu, o2, o);
                    }
                    if (lane < 16 && p < kAccPackets) {
                        if (r < 3 - (p % 27 == 26))
                            P.out[b * 640 + (p / 27) * 80 + 3 * (p % 27) + r] = __float2bfloat16_rn(r == 0 ? o0 : r == 1 ? o1 : o2);
                        *src = make_float4(0.f, 0.f, 0.f, 0.f);
                        if (r == 0) g_acc[b][2][p] = make_float4(0.f, 0.f, 0.f, 0.f);
                    }
                    TRACE_G(15);
                }
            }
        }
    }
}

struct Sched {
    Params& P;
    int np = 0, nm = 0, nl = 0, rslot = 0, mark = 0, lateRet = 0;
    uint32_t pending = 0;
    enum { RF = 1 << 7, FIRST = 1 << 11, PUB = 1 << 12 };
    void low_begin(int back) { mark = nl - back; }
    void low_end(int back) { for (int i = mark; i < nl - back; i++) P.loads[i] |= LD_LOW; }
    void slot(uint32_t e, int s) { P.loads[nl++] = e | (s << 4); }
    void ring(uint32_t e) {
        slot(e | pending, rslot);
        pending = 0;
        rslot = (rslot + 1) % kRing;
    }
    static uint32_t tile(int isB, int b, int idx, int v) {
        return LD_VALID | (2 * isB + v) | (uint32_t)(b * 32 * 4096 + 64 * idx) << 10;
    }
    static uint32_t wq(int layer, int p) { return LD_VALID | (4 + (layer & 1)) | (p == 2 ? 96 : 64 * p) << 10; }
    static uint32_t wo(int layer, int p) { return LD_VALID | (6 + (layer & 1)) | (16 * p) << 10; }
    void kv(int isB, int b, int idx, uint32_t fk = 0, uint32_t fv = 0) {
        ring(tile(isB, b, idx, 0) | fk);
        ring(tile(isB, b, idx, 1) | fv);
    }
    void ret(int b, int idx, int pair) {
        slot(tile(1, b, idx, 0), kRing + 2 * pair);
        slot(tile(1, b, idx, 1), kRing + 2 * pair + 1);
    }
    const char* wuse = "";
    uint32_t wflags() {
        const char c = *wuse ? *wuse++ : '-';
        return ((c == 'k' || c == 'b') ? LD_KEEP : 0u) | ((c == 'h' || c == 'b') ? LD_HIT : 0u);
    }
    void qproj(int mask, int layer, uint32_t f = 0, bool anchor = true) {
        f |= wflags();
        for (int p = 0; p < 3; p++) ring(wq(layer, p) | f);
        if (anchor) pending = LD_ANCHOR;
        P.prog[np++] = OP_QPROJ | (mask << 3) | (layer << 5);
        for (int b = 0; b < 2; b++)
            if ((mask >> b) & 1) P.merge[nm++] = MG_Q | (b << 2) | (layer << 3);
    }
    void oproj(int mask, int layer, uint32_t f = 0, int firstSlot = 0) {
        f |= wflags();
        if (!firstSlot) for (int p = 0; p < 3; p++) ring(wo(layer, p) | f);
        P.prog[np++] = OP_OPROJ | (mask << 3) | (layer << 5) | (firstSlot << 8);
    }
    void rfload(int pair, int isB, int b, int idx) {
        kv(isB, b, idx);
        P.prog[np++] = OP_RFLOAD | (pair << 3);
    }
    void seg(int b, int layer, uint32_t flags, const char* order, int nrel = 0) {
        uint64_t list = 0;
        int nr = 0;
        for (int n = 0; order[n]; n++) {
            const char c = order[n];
            uint64_t it = 12;
            if (c == 'r') { it = 8 | (nr < nrel ? 4 : 0) | (nr % 3 + 1); nr++; }
            else if (c >= 'a' && c <= 'c') it = 12 | (c - 'a' + 1);
            else if (c >= 'A' && c <= 'C') it = 8 | (c - 'A' + 1);
            list |= it << (4 * n);
        }
        P.prog[np++] = OP_SEG | (b << 3) | ((layer & 1) << 4) | (flags & RF);
        P.prog[np++] = (uint32_t)list;
        P.prog[np++] = (uint32_t)(list >> 32);
        P.merge[nm++] = MG_ATTN | (b << 2) | (layer << 3) | ((flags & FIRST) ? 32 : 0) | ((flags & PUB) ? 64 : 0);
    }
    void seg(int b, int layer, uint32_t flags, int nring) { seg(b, layer, flags, &"dddddddddddddddd"[16 - nring]); }
};

const char* tune_str(const char* name, const char* dflt) {
    (void)name;
    return dflt;
}

int tune(const char* name, int dflt) {
    (void)name;
    return dflt;
}

void build_schedule(Params& P) {
    for (int i = 0; i < kMaxProg; i++) P.prog[i] = P.merge[i] = 0;
    for (int i = 0; i < kMaxLoads; i++) P.loads[i] = LD_NONE;
    P.winLow = tune("WINLOW", 3);
    P.winHigh = tune("WINHIGH", 3);
    P.tau = tune("TAU", 970);
    P.tauLow = tune("TAULOW", 1010);
    P.tauW = tune("TAUW", P.tauLow * 5 / 6);
    P.credit = tune("CREDIT", 700);
    P.anchorDelay = tune("ADELAY", 200);
    P.startDelay = tune("STARTDELAY", 1000);
    P.look = tune("LOOK", 4);
    P.lookBack = tune("LOOKBACK", 0);
    P.hitTouch = tune("HITTOUCH", 0);
    P.nStart = tune("NSTART", 10);
    P.winStart = tune("WINSTART", 5);
    P.lookFar = tune("LOOKFAR", 4);

    Sched S{P};
    using F = Sched;
    S.wuse = tune_str("WK", "k-k-h-h-----");
    const int keep[2] = {tune("KEEP0", 9), tune("KEEP1", 10)};
    auto flag = [&](int b, int idx, int v, uint32_t f) { return (2 * (15 - idx) + (1 - v)) < keep[b] ? f : 0u; };
    const int hit[2] = {16 - (keep[0] + 1) / 2, 16 - (keep[1] + 1) / 2};
    int next0 = 3, next1 = 7, nextA = 0;
    auto first0 = [&](const char* order, uint32_t flags) {
        for (const char* c = order; *c; c++)
            if (*c != 'r') {
                S.kv(1, 0, next0, flag(0, next0, 0, LD_KEEP), flag(0, next0, 1, LD_KEEP));
                if (++next0 == 5) for (; S.lateRet > 0; S.lateRet--) S.ret(0, 3 - S.lateRet, 3 - S.lateRet);
            }
        S.seg(0, 1, flags, order);
    };
    auto fillA = [&](const char* order, uint32_t flags) {
        int nr = 0;
        for (const char* c = order; *c; c++) if (*c == 'r') nr++; else S.kv(0, 1, nextA++);
        S.seg(1, 0, flags, order, nr);
    };
    auto fill0 = [&](int n, uint32_t flags = 0) {
        int c = 0;
        for (; c < n && next0 < hit[0]; c++) S.kv(1, 0, next0++);
        if (c > 0 || flags) S.seg(0, 3, flags, c);
    };
    auto fill1 = [&](int n) {
        int c = 0;
        const uint32_t flags = next1 == 7 ? F::FIRST : 0;
        for (; c < n && next1 < hit[1]; c++) S.kv(1, 1, next1++);
        if (c > 0) S.seg(1, 1, flags, c);
    };
    int nextH[2] = {hit[0], hit[1]}, nextK = hit[1], nextD1 = 10;
    bool started[2] = {};
    auto phase = [&](const char* spec, const int (&layer)[2], int refill0, const char* pos, int pubMask) {
        int tiles = 0, nq = 0, done = 0, due[8];
        uint32_t ent[8];
        auto flush = [&](int upto) { while (done < nq && due[done] <= upto) P.loads[S.nl++] = ent[done++]; };
        for (const char* c = spec; *c; c++) {
            if (!nq && (*c == 'h' || *c == 'd' || *c == 'k')) tiles += 2;
            if (*c >= 'a' && *c <= 'c')
                for (int v = 0; v < 2; v++, nq++) {
                    due[nq] = tiles + (pos[nq] <= '9' ? pos[nq] - '0' : pos[nq] - 'a' + 10);
                    ent[nq] = F::tile(1, 1, refill0 + nq / 2, v) | LD_FAR | ((kRing + 2 * (*c - 'a') + v) << 4);
                }
        }
        tiles = 0;
        for (const char* c = spec; *c;) {
            const int b = *c++ - '0';
            char order[20];
            int n = 0;
            uint32_t flags = started[b] ? 0 : F::FIRST;
            started[b] = true;
            for (; *c && *c != '.'; c++) {
                if (*c == 'R') { flags |= F::RF; continue; }
                order[n++] = *c;
                if (*c != 'h' && *c != 'd' && *c != 'k') continue;
                const int idx = *c == 'h' ? nextH[b]++ : *c == 'k' ? nextK++ : b ? nextD1++ : next0++;
                for (int v = 0; v < 2; v++, tiles++) {
                    flush(tiles);
                    S.ring(F::tile(1, b, idx, v) | LD_FAR | flag(b, idx, v, *c == 'h' ? LD_HIT : *c == 'k' ? LD_KEEP : 0));
                }
            }
            order[n] = 0;
            bool last = true;
            for (const char* r = c; *r; r++) if (*r == '.' && r[1] - '0' == b) last = false;
            S.seg(b, layer[b], flags | ((last && ((pubMask >> b) & 1)) ? F::PUB : 0), order);
            if (*c) c++;
        }
        flush(1 << 20);
    };

    P.exp = tune("EXP", 0);
    if (P.exp) {
        S.qproj(3, 0);
        for (int r = 0; r < 2; r++)
            for (int b = 0; b < 2; b++) {
                for (int i = 0; i < 15; i++) S.kv(1, b, i);
                S.seg(b, 0, F::FIRST, 15);
            }
        return;
    }
    const int lb = tune("LOWBACK", 0);
    const int early = tune("EARLY", 1);
    S.qproj(3, 0, 0, false);
    for (int i = 0; i < early; i++) {
        S.slot(F::tile(0, 1, i, 0), kRing + 2 * i);
        S.slot(F::tile(0, 1, i, 1), kRing + 2 * i + 1);
    }
    for (int i = 0; i < 4; i++) S.rfload(i, 0, 0, i);
    S.seg(0, 0, F::RF | F::FIRST | F::PUB, 0);
    S.low_begin(lb);
    if (tune("JOINT", 1)) {
        nextA = early;
        fillA(tune_str("LA", "rddd"), F::FIRST | F::PUB);
        const int late = tune("RETLATE", 0);
        S.oproj(3, 0);
        for (int i = 0; i < 3 - late; i++) S.ret(0, i, i);
        S.qproj(3, 1);
        S.low_end(0);
        S.lateRet = late;
        first0(tune_str("L2", "dddrdddrdddrdddd"), F::FIRST | F::PUB);
    } else {
        nextA = early;
        fillA(tune_str("LA1", "d"), F::FIRST);
        S.oproj(1, 0, LD_KEEP);
        fillA(tune_str("LA2", "ddd"), F::PUB);
        S.qproj(1, 1, LD_KEEP);
        S.pending = 0;
        P.loads[S.nl] = 0;
        S.ret(0, 0, 0);
        P.loads[S.nl - 2] |= tune("RETANCHOR", 0) ? LD_ANCHOR : 0;
        S.oproj(2, 0, LD_HIT);
        S.ret(0, 1, 1);
        S.ret(0, 2, 2);
        first0(tune_str("L2A", "ddd"), F::FIRST);
        S.qproj(2, 1, LD_HIT);
        S.low_end(0);
        first0(tune_str("L2B", "drddrddrddddd"), F::PUB);
    }
    next0 = 3;
    S.low_begin(lb);
    fill1(tune("F21", 0));
    S.oproj(1, 1);
    fill1(tune("F22", 2));
    S.qproj(1, 2);
    fill1(tune("F23", 1));
    S.seg(0, 2, F::RF | F::FIRST | F::PUB, 0);
    const int r1 = tune("R31", 1), r2 = r1 + tune("R32", 2);
    for (int i = 0; i < r1; i++) S.rfload(i, 1, 1, 3 + i);
    fill1(tune("F31", 0));
    S.oproj(1, 2);
    for (int i = r1; i < r2; i++) S.rfload(i, 1, 1, 3 + i);
    fill1(tune("F32", 1));
    S.qproj(1, 3);
    for (int i = r2; i < 4; i++) S.rfload(i, 1, 1, 3 + i);
    fill1(16);
    S.low_end(0);
    started[1] = next1 > 7;
    phase(tune_str("P4", "0ahbchhhh.1RkkkAkBCk"), {3, 1}, 0, tune_str("POS4", "334577"), 2);
    S.low_begin(lb);
    fill0(tune("F41", 0));
    S.oproj(2, 1);
    fill0(tune("F42", 2));
    S.qproj(2, 2);
    fill0(tune("F43", 1));
    for (int i = 0; i < 4; i++) S.kv(0, 1, i);
    S.seg(1, 2, F::FIRST | F::PUB, 4);
    fill0(tune("F51", 1));
    S.oproj(2, 2);
    fill0(tune("F52", 2));
    S.qproj(2, 3);
    fill0(tune("F53", 0));
    S.low_end(0);
    started[1] = false;
    phase(tune_str("P6", "0dd.1RabdchhhAhBhC"), {3, 3}, 7, tune_str("POS6", "33579b"), 3);
    S.oproj(3, 3);
}

typedef CUresult (*EncodeFn)(CUtensorMap*, CUtensorMapDataType, cuuint32_t, void*, const cuuint64_t*,
                             const cuuint64_t*, const cuuint32_t*, const cuuint32_t*, CUtensorMapInterleave,
                             CUtensorMapSwizzle, CUtensorMapL2promotion, CUtensorMapFloatOOBfill);

}

extern "C" void kernel_launch(void* const* d_in, const int* in_sizes, int n_in, void* d_out, int out_size) {
    (void)in_sizes; (void)n_in; (void)out_size;
    Params P;
    void* fn = nullptr;
    cudaDriverEntryPointQueryResult qr;
    cudaGetDriverEntryPoint("cuTensorMapEncodeTiled", &fn, cudaEnableDefault, &qr);
    EncodeFn encode = reinterpret_cast<EncodeFn>(fn);
    const CUtensorMapL2promotion promo = (CUtensorMapL2promotion)tune("PROMO", CU_TENSOR_MAP_L2_PROMOTION_NONE);
    void* kv[4] = {d_in[1], d_in[2], d_in[6], d_in[7]};
    for (int i = 0; i < 4; i++) {
        const cuuint64_t dims[3] = {64, 2ull * 32 * 4096, 3};
        const cuuint64_t strides[2] = {384, 128};
        const cuuint32_t box[3] = {64, 64, 3};
        const cuuint32_t es[3] = {1, 1, 1};
        encode(&P.tm[i], CU_TENSOR_MAP_DATA_TYPE_BFLOAT16, 3, kv[i], dims, strides, box, es,
               CU_TENSOR_MAP_INTERLEAVE_NONE, CU_TENSOR_MAP_SWIZZLE_128B, promo, CU_TENSOR_MAP_FLOAT_OOB_FILL_NONE);
    }
    void* wq[2] = {d_in[3], d_in[8]};
    for (int i = 0; i < 2; i++) {
        const cuuint64_t dims[3] = {64, 640, 96};
        const cuuint64_t strides[2] = {12288, 128};
        const cuuint32_t box[3] = {64, 64, 3};
        const cuuint32_t es[3] = {1, 1, 1};
        encode(&P.tm[4 + i], CU_TENSOR_MAP_DATA_TYPE_BFLOAT16, 3, wq[i], dims, strides, box, es,
               CU_TENSOR_MAP_INTERLEAVE_NONE, CU_TENSOR_MAP_SWIZZLE_128B, promo, CU_TENSOR_MAP_FLOAT_OOB_FILL_NONE);
    }
    void* wo[2] = {d_in[4], d_in[9]};
    for (int i = 0; i < 2; i++) {
        const cuuint64_t dims[3] = {64, 6144, 10};
        const cuuint64_t strides[2] = {1280, 128};
        const cuuint32_t box[3] = {64, 16, 10};
        const cuuint32_t es[3] = {1, 1, 1};
        encode(&P.tm[6 + i], CU_TENSOR_MAP_DATA_TYPE_BFLOAT16, 3, wo[i], dims, strides, box, es,
               CU_TENSOR_MAP_INTERLEAVE_NONE, CU_TENSOR_MAP_SWIZZLE_128B, promo, CU_TENSOR_MAP_FLOAT_OOB_FILL_NONE);
    }
    P.x = static_cast<const __nv_bfloat16*>(d_in[0]);
    P.out = static_cast<__nv_bfloat16*>(d_out);
    build_schedule(P);
    cudaFuncSetAttribute(fused_decode_kernel, cudaFuncAttributeMaxDynamicSharedMemorySize, kSmemBytes);
    fused_decode_kernel<<<kCtas, kThreads, kSmemBytes>>>(P);
}
```

```cpp
#include <cuda_runtime.h>
#include <cuda_bf16.h>
#include <cuda.h>
#include <stdint.h>

namespace {

constexpr int kCtas = 128;
constexpr int kThreads = 384;
constexpr int kSlotBytes = 3072;
constexpr int kRing = 3;
constexpr int kSlots = 9;
constexpr int kWRow = 192;

constexpr int kOffWbuf = kSlots * 8 * kSlotBytes;
constexpr int kOffMl = kOffWbuf + 8 * kWRow * 4;
constexpr int kOffCpart = kOffMl + 20 * 4;
constexpr int kOffQf = kOffCpart + 2 * kWRow * 4;
constexpr int kOffXn = kOffQf + 2 * 96 * 4;
constexpr int kOffObf = kOffXn + 2 * 160 * 2;
constexpr int kOffFull = kOffObf + 2 * 48 * 2;
constexpr int kOffEmpty = kOffFull + kSlots * 8;
constexpr int kOffSync = kOffEmpty + kSlots * 8;
constexpr int kOffAnchor = kOffSync + 14 * 8;
constexpr int kSmemBytes = kOffAnchor + 8;
static_assert(kSmemBytes <= 232448, "shared memory budget");
constexpr int kBarRows = 0, kBarFree = 8, kBarQ = 16, kBarXn = 32, kBarO = 48;
constexpr int kBarSentQ = 64, kBarSentP = 80, kBarSentY = 96;

constexpr int kMaxProg = 112;
constexpr int kMaxLoads = 200;

enum : uint32_t { OP_END = 0, OP_QPROJ = 1, OP_RFLOAD = 2, OP_SEG = 3, OP_OPROJ = 4 };
enum : uint32_t { LD_NONE = 0, LD_KEEP = 1u << 3, LD_LOW = 1u << 8, LD_VALID = 1u << 9, LD_ANCHOR = 1u << 29, LD_FAR = 1u << 30, LD_HIT = 1u << 31 };
enum : uint32_t { MG_END = 0, MG_ATTN = 1, MG_Q = 2 };

struct alignas(64) Params {
    CUtensorMap tm[8];
    const __nv_bfloat16* x;
    __nv_bfloat16* out;
    uint32_t winLow, winHigh;
    uint32_t tau, tauLow, tauW, credit;
    uint32_t look, lookBack, lookFar, nStart, winStart;
    uint32_t anchorDelay[6], anchorCredit[6], startDelay, keepFirst;
    uint32_t exp;
    uint32_t prog[kMaxProg];
    uint32_t merge[kMaxProg];
    uint32_t loads[kMaxLoads];
};

__device__ uint4 g_q[2][32][4][40];
__device__ uint4 g_p[2][32][4][4][18];
constexpr int kAccPackets = 216;
constexpr float kAccDone = 129.f;
__device__ float4 g_acc[2][3][kAccPackets];
constexpr int kOutReplicas = 8;
__device__ float4 g_out[2][kOutReplicas][kAccPackets];

#define SLEEPNS 200
#define SLEEPQ 0
constexpr uint32_t kSpinLimit = 1u << 22;

__device__ __forceinline__ void mbar_init(uint32_t bar, uint32_t count) {
    asm volatile("mbarrier.init.shared::cta.b64 [%0], %1;" ::"r"(bar), "r"(count) : "memory");
}
__device__ __forceinline__ void mbar_arrive(uint32_t bar) {
    asm volatile("mbarrier.arrive.shared::cta.b64 _, [%0];" ::"r"(bar) : "memory");
}
__device__ __forceinline__ bool mbar_test(uint32_t bar, uint32_t parity) {
    uint32_t ok;
    asm volatile(
        "{\n\t.reg .pred p;\n\t"
        "mbarrier.test_wait.parity.shared::cta.b64 p, [%1], %2;\n\t"
        "selp.u32 %0, 1, 0, p;\n\t}"
        : "=r"(ok) : "r"(bar), "r"(parity) : "memory");
    return __all_sync(0xffffffffu, ok);
}
__device__ __forceinline__ void mbar_expect(uint32_t bar, uint32_t bytes) {
    asm volatile("mbarrier.arrive.expect_tx.shared::cta.b64 _, [%0], %1;" ::"r"(bar), "r"(bytes) : "memory");
}
__device__ __forceinline__ void mbar_wait(uint32_t bar, uint32_t parity) {
    uint32_t ok, it = 0;
    do {
        asm volatile(
            "{\n\t.reg .pred p;\n\t"
            "mbarrier.try_wait.parity.shared::cta.b64 p, [%1], %2;\n\t"
            "selp.u32 %0, 1, 0, p;\n\t}"
            : "=r"(ok) : "r"(bar), "r"(parity) : "memory");
        if (++it > kSpinLimit) __trap();
    } while (!ok);
}
__device__ __forceinline__ bool mbar_try(uint32_t bar, uint32_t parity) {
    uint32_t ok;
    asm volatile(
        "{\n\t.reg .pred p;\n\t"
        "mbarrier.try_wait.parity.shared::cta.b64 p, [%1], %2;\n\t"
        "selp.u32 %0, 1, 0, p;\n\t}"
        : "=r"(ok) : "r"(bar), "r"(parity) : "memory");
    return __all_sync(0xffffffffu, ok);
}
__device__ __forceinline__ void mbar_wait_u(uint32_t bar, uint32_t parity) {
    for (uint32_t it = 0; !mbar_try(bar, parity); it++)
        if (it > kSpinLimit) __trap();
}
__device__ __forceinline__ void prefetch_l2(const void* p) {
    asm volatile("prefetch.global.L2 [%0];" ::"l"(p) : "memory");
}
__device__ __forceinline__ void tma3d(uint32_t dst, const CUtensorMap* tm, int c0, int c1, int c2, uint32_t bar, uint64_t pol) {
    asm volatile(
        "cp.async.bulk.tensor.3d.shared::cluster.global.mbarrier::complete_tx::bytes.L2::cache_hint "
        "[%0], [%1, {%2, %3, %4}], [%5], %6;"
        ::"r"(dst), "l"(tm), "r"(c0), "r"(c1), "r"(c2), "r"(bar), "l"(pol) : "memory");
}
__device__ __forceinline__ void tma3d_prefetch(const CUtensorMap* tm, int c0, int c1, int c2, uint64_t pol) {
    asm volatile("cp.async.bulk.prefetch.tensor.3d.L2.global.L2::cache_hint [%0, {%1, %2, %3}], %4;"
                 ::"l"(tm), "r"(c0), "r"(c1), "r"(c2), "l"(pol) : "memory");
}
__device__ __forceinline__ uint64_t make_policy(bool keep) {
    uint64_t pol;
    if (keep) asm volatile("createpolicy.fractional.L2::evict_normal.b64 %0, 1.0;" : "=l"(pol));
    else      asm volatile("createpolicy.fractional.L2::evict_first.b64 %0, 1.0;" : "=l"(pol));
    return pol;
}
__device__ __forceinline__ void ldsm4(uint32_t (&r)[4], uint32_t addr) {
    asm volatile("ldmatrix.sync.aligned.m8n8.x4.shared.b16 {%0,%1,%2,%3}, [%4];"
                 : "=r"(r[0]), "=r"(r[1]), "=r"(r[2]), "=r"(r[3]) : "r"(addr) : "memory");
}
__device__ __forceinline__ void ldsm4t(uint32_t (&r)[4], uint32_t addr) {
    asm volatile("ldmatrix.sync.aligned.m8n8.x4.trans.shared.b16 {%0,%1,%2,%3}, [%4];"
                 : "=r"(r[0]), "=r"(r[1]), "=r"(r[2]), "=r"(r[3]) : "r"(addr) : "memory");
}
__device__ __forceinline__ void mma16816(float (&c)[4], const uint32_t (&a)[4], uint32_t b0, uint32_t b1) {
    asm volatile("mma.sync.aligned.m16n8k16.row.col.f32.bf16.bf16.f32 {%0,%1,%2,%3}, {%4,%5,%6,%7}, {%8,%9}, {%0,%1,%2,%3};"
                 : "+f"(c[0]), "+f"(c[1]), "+f"(c[2]), "+f"(c[3])
                 : "r"(a[0]), "r"(a[1]), "r"(a[2]), "r"(a[3]), "r"(b0), "r"(b1));
}
__device__ __forceinline__ float bf16r(float v) { return __bfloat162float(__float2bfloat16_rn(v)); }
__device__ __forceinline__ uint32_t pack_bf16(float lo, float hi) {
    uint32_t r;
    asm("cvt.rn.bf16x2.f32 %0, %1, %2;" : "=r"(r) : "f"(hi), "f"(lo));
    return r;
}
__device__ __forceinline__ bool elect() {
    uint32_t p;
    asm volatile("{\n\t.reg .pred e;\n\telect.sync _|e, 0xffffffff;\n\tselp.u32 %0, 1, 0, e;\n\t}" : "=r"(p));
    return p;
}
__device__ __forceinline__ float fast_sqrt(float v) {
    float r;
    asm("sqrt.approx.f32 %0, %1;" : "=f"(r) : "f"(v));
    return r;
}
__device__ __forceinline__ float ex2(float v) {
    float r;
    asm("ex2.approx.ftz.f32 %0, %1;" : "=f"(r) : "f"(v));
    return r;
}
__device__ __forceinline__ void st_packet(uint4* p, uint32_t a, uint32_t b, uint32_t c, uint32_t tag) {
    asm volatile(
        "{\n\t.reg .b64 lo, hi;\n\t.reg .b128 v;\n\t"
        "mov.b64 lo, {%1, %2};\n\tmov.b64 hi, {%3, %4};\n\tmov.b128 v, {lo, hi};\n\t"
        "st.relaxed.gpu.global.b128 [%0], v;\n\t}"
        ::"l"(p), "r"(a), "r"(b), "r"(c), "r"(tag) : "memory");
}
__device__ __forceinline__ void st_packet(uint4* p, float a, float b, float c, uint32_t tag) {
    st_packet(p, __float_as_uint(a), __float_as_uint(b), __float_as_uint(c), tag);
}
__device__ __forceinline__ uint4 ld_packet(const uint4* p) {
    uint4 v;
    asm volatile(
        "{\n\t.reg .b64 lo, hi;\n\t.reg .b128 v;\n\t"
        "ld.relaxed.gpu.global.b128 v, [%4];\n\t"
        "mov.b128 {lo, hi}, v;\n\tmov.b64 {%0, %1}, lo;\n\tmov.b64 {%2, %3}, hi;\n\t}"
        : "=r"(v.x), "=r"(v.y), "=r"(v.z), "=r"(v.w) : "l"(p) : "memory");
    return v;
}
__device__ __forceinline__ void red_packet(float4* p, float a, float b, float c) {
    asm volatile("red.relaxed.gpu.global.add.v4.f32 [%0], {%1, %2, %3, %4};"
                 ::"l"(p), "f"(a), "f"(b), "f"(c), "f"(1.f) : "memory");
}
#define POLL_UNTIL(pause, loads, done)            \
    for (uint32_t it_ = 0;; it_++) {              \
        loads;                                    \
        if (__all_sync(0xffffffffu, done)) break; \
        if (it_ > kSpinLimit) __trap();           \
        if (pause) __nanosleep(pause);            \
    }
__device__ __forceinline__ uint32_t round24(float v) {
    const uint32_t u = __float_as_uint(v);
    return u + ((u & 0x7f800000u) == 0x7f800000u ? 0u : 0x80u);
}
__device__ __forceinline__ void st_packet5(uint4* p, const float* v, uint32_t tag) {
    const uint32_t r0 = round24(v[0]), r1 = round24(v[1]), r2 = round24(v[2]), r3 = round24(v[3]), r4 = round24(v[4]);
    st_packet(p, __byte_perm(r0, r1, 0x5321), __byte_perm(r1, r2, 0x6532), __byte_perm(r2, r3, 0x7653),
              (r4 >> 8) | (tag << 24));
}
__device__ __forceinline__ void add_packet5(float (&a)[5], const uint4& v) {
    a[0] += __uint_as_float(v.x << 8);
    a[1] += __uint_as_float(__funnelshift_r(v.x, v.y, 16) & 0xffffff00u);
    a[2] += __uint_as_float(__funnelshift_r(v.y, v.z, 8) & 0xffffff00u);
    a[3] += __uint_as_float(v.z & 0xffffff00u);
    a[4] += __uint_as_float(v.w << 8);
}
__device__ __forceinline__ uint32_t now_ns() {
    uint32_t t;
    asm volatile("mov.u32 %0, %globaltimer_lo;" : "=r"(t));
    return t;
}
__device__ __forceinline__ float bf_lo(uint32_t v) { return __uint_as_float(v << 16); }
__device__ __forceinline__ float bf_hi(uint32_t v) { return __uint_as_float(v & 0xffff0000u); }
__device__ __forceinline__ float warp_sum(float v) {
#pragma unroll
    for (int o = 16; o > 0; o >>= 1) v += __shfl_xor_sync(0xffffffffu, v, o);
    return v;
}

constexpr float kScale = 0.07216878364870322f * 1.4426950408889634f;

struct Attn {
    float m, l;
    float acc[3][4];
};

__device__ __forceinline__ uint32_t probability(Attn& st, float s) {
    const float e = ex2(s - st.m);
    st.l += e;
    const float hi = bf16r(e);
    const uint32_t hl = pack_bf16(hi, e - hi);
    uint32_t pv;
    asm volatile("movmatrix.sync.aligned.m8n8.trans.b16 %0, %1;" : "=r"(pv) : "r"(hl));
    return pv;
}

__device__ __forceinline__ uint32_t softmax_step(Attn& st, float s) {
    if (__any_sync(0xffffffffu, s > st.m)) {
        float mx = fmaxf(s, __shfl_xor_sync(0xffffffffu, s, 4));
        mx = fmaxf(mx, __shfl_xor_sync(0xffffffffu, mx, 8));
        mx = fmaxf(mx, __shfl_xor_sync(0xffffffffu, mx, 16));
        mx = fmaxf(mx, st.m);
        const float corr = ex2(st.m - mx);
        st.m = mx;
        st.l *= corr;
#pragma unroll
        for (int a = 0; a < 3; a++)
#pragma unroll
            for (int i = 0; i < 4; i++) st.acc[a][i] *= corr;
    }
    return probability(st, s);
}

#define TRACE_G(i)
#define TRACE_C(i)

__global__ void __launch_bounds__(kThreads, 1)
fused_decode_kernel(const __grid_constant__ Params P) {
    extern __shared__ __align__(1024) unsigned char smem[];
    const uint32_t sbase = (uint32_t)__cvta_generic_to_shared(smem);
    const uint32_t sync0 = sbase + kOffSync;
    float* const wbuf = reinterpret_cast<float*>(smem + kOffWbuf);

    const int lane = threadIdx.x & 31;
    const int w = __shfl_sync(0xffffffffu, threadIdx.x >> 5, 0);
    const int cta = blockIdx.x;
    const int h = cta >> 2, jq = cta & 3;

    if (w >= 10) {
        const int i0 = 80 * (w - 10) + lane;
#pragma unroll
        for (int i = 0; i < 3; i++)
            if (i < 2 || lane < 16)
                asm volatile("cp.async.cg.shared.global [%0], [%1], 16;"
                             ::"r"(sbase + kOffWbuf + 16 * (i0 + 32 * i)), "l"(reinterpret_cast<const uint4*>(P.x) + i0 + 32 * i) : "memory");
    }
    if (elect()) {
        if (w == 8) {
#pragma unroll
            for (int i = 0; i < kSlots; i++) {
                mbar_init(sbase + kOffFull + 8 * i, 1);
                mbar_init(sbase + kOffEmpty + 8 * i, 8);
            }
        } else if (w == 9) {
#pragma unroll
            for (int i = 0; i < 8; i++) asm volatile("prefetch.tensormap [%0];" ::"l"(&P.tm[i]) : "memory");
        } else if (w == 10) {
#pragma unroll
            for (int i = 0; i < 14; i++) mbar_init(sync0 + 8 * i, (8 * i == kBarRows || 8 * i >= kBarSentY) ? 8 : 1);
        }
        if (w != 9) asm volatile("fence.mbarrier_init.release.cluster;" ::: "memory");
    }
    __syncwarp();
    if (w == 8) {
        asm volatile("bar.arrive 1, %0;" ::"n"(kThreads) : "memory");
    } else {
        asm volatile("bar.sync 1, %0;" ::"n"(kThreads) : "memory");
    }

    if (w < 8) {
        asm volatile("setmaxnreg.inc.sync.aligned.u32 232;");
        const uint32_t full0 = sbase + kOffFull;
        const uint32_t frag0 = sbase + w * 1024 + (lane & 7) * 128 + (((lane >> 3) ^ (lane & 7)) << 4), frag1 = frag0 ^ 64;
        auto frag_addr = [&](uint32_t s, int k) { return ((k & 1) ? frag1 : frag0) + s * (8 * kSlotBytes) + (k >> 1) * 8192; };
        uint32_t par = 0, rpos = 0, nrows = 0;
        auto wait_tile = [&](uint32_t s) { mbar_wait(full0 + 8 * s, (par >> s) & 1u); };
        auto tile_ready = [&](uint32_t s) { return mbar_test(full0 + 8 * s, (par >> s) & 1u); };
        auto release = [&](uint32_t s) {
            par ^= 1u << s;
            __syncwarp();
            if (elect()) mbar_arrive(full0 + 8 * s + (kOffEmpty - kOffFull));
        };
        auto ring_release = [&]() {
            release(rpos);
            if (++rpos == kRing) rpos = 0;
        };
        auto row_acquire = [&]() { mbar_wait(sync0 + kBarFree, (nrows & 1) ^ 1); };
        auto row_publish = [&]() {
            __syncwarp();
            if (elect()) mbar_arrive(sync0 + kBarRows);
            nrows++;
        };

        uint32_t rf[8][6][4];
#pragma unroll
        for (int i = 0; i < 8; i++)
#pragma unroll
            for (int s = 0; s < 6; s++)
#pragma unroll
                for (int k = 0; k < 4; k++) rf[i][s][k] = 0;

#pragma unroll 1
        for (int pc = 0;; pc++) {
            const uint32_t op = P.prog[pc];
            const uint32_t kind = op & 7u;
            if (kind == OP_END) break;
            int lane = threadIdx.x & 31;
            asm volatile("" : "+r"(lane));
            const int g = lane >> 2, t = lane & 3;
            float* const row = wbuf + w * kWRow;

            if (kind == OP_SEG) {
                const uint32_t b = (op >> 3) & 1u;
                mbar_wait(sync0 + kBarQ + 8 * b, (op >> 4) & 1u);
                const uint2* qf = reinterpret_cast<const uint2*>(smem + kOffQf) + b * 48 + (lane & 7);
                Attn st;
                st.m = -INFINITY; st.l = 0.f;
#pragma unroll
                for (int a = 0; a < 3; a++)
#pragma unroll
                    for (int i = 0; i < 4; i++) st.acc[a][i] = 0.f;

                if (op & (1u << 7)) {
                    float c[4][4] = {};
#pragma unroll
                    for (int k = 0; k < 6; k++) {
                        const uint2 q = qf[8 * k];
#pragma unroll
                        for (int i = 0; i < 4; i++) mma16816(c[i], rf[2 * i][k], q.x, q.y);
                    }
                    float sc[4];
#pragma unroll
                    for (int i = 0; i < 4; i++) sc[i] = (c[i][0] + c[i][3]) * kScale;
                    float mx = fmaxf(fmaxf(sc[0], sc[1]), fmaxf(sc[2], sc[3]));
                    mx = fmaxf(mx, __shfl_xor_sync(0xffffffffu, mx, 4));
                    mx = fmaxf(mx, __shfl_xor_sync(0xffffffffu, mx, 8));
                    st.m = fmaxf(mx, __shfl_xor_sync(0xffffffffu, mx, 16));
                    uint32_t pv[4];
#pragma unroll
                    for (int i = 0; i < 4; i++) pv[i] = probability(st, sc[i]);
#pragma unroll
                    for (int i = 0; i < 4; i++)
#pragma unroll
                        for (int k = 0; k < 6; k++)
                            mma16816(st.acc[k >> 1], rf[2 * i + 1][k], (g >> 1) == 2 * (k & 1) ? pv[i] : 0u,
                                     (g >> 1) == 2 * (k & 1) + 1 ? pv[i] : 0u);
                }

                uint32_t lo = P.prog[pc + 1], hi = P.prog[pc + 2];
                pc += 2;
                bool haveK = false;
#pragma unroll 1
                while (lo & 15u) {
                    const bool rel = lo & 4u;
                    uint32_t sK = kRing - 2 + 2 * (lo & 3u), sV = sK + 1;
                    if (!(lo & 3u)) {
                        sK = rpos;
                        sV = rpos == kRing - 1 ? 0 : rpos + 1;
                        rpos = sV == kRing - 1 ? 0 : sV + 1;
                    }
                    lo = __funnelshift_r(lo, hi, 4);
                    hi >>= 4;
                    if (!haveK) wait_tile(sK);
                    const bool haveV = tile_ready(sV);
                    float c[2][4] = {};
#pragma unroll
                    for (int k = 0; k < 6; k++) {
                        uint32_t a[4];
                        ldsm4(a, frag_addr(sK, k));
                        const uint2 q = qf[8 * k];
                        mma16816(c[k & 1], a, q.x, q.y);
                    }
                    if (rel) release(sK);
                    const uint32_t pv = softmax_step(st, ((c[0][0] + c[0][3]) + (c[1][0] + c[1][3])) * kScale);
                    if (!haveV) wait_tile(sV);
                    haveK = tile_ready((lo & 3u) ? kRing - 2 + 2 * (lo & 3u) : rpos);
#pragma unroll
                    for (int k = 0; k < 6; k++) {
                        uint32_t a[4];
                        ldsm4t(a, frag_addr(sV, k));
                        mma16816(st.acc[k >> 1], a, (g >> 1) == 2 * (k & 1) ? pv : 0u, (g >> 1) == 2 * (k & 1) + 1 ? pv : 0u);
                    }
                    if (rel) release(sV);
                }

                TRACE_C(4);
                float l = st.l;
                l += __shfl_xor_sync(0xffffffffu, l, 4);
                l += __shfl_xor_sync(0xffffffffu, l, 8);
                l += __shfl_xor_sync(0xffffffffu, l, 16);
                row_acquire();
#pragma unroll
                for (int a = 0; a < 3; a++) {
                    row[64 * a + 16 * t + g] = st.acc[a][0] + st.acc[a][1];
                    row[64 * a + 16 * t + g + 8] = st.acc[a][2] + st.acc[a][3];
                }
                if (lane == 0) { wbuf[8 * kWRow + w] = st.m; wbuf[8 * kWRow + 8 + w] = l; }
                row_publish();
            } else if (kind == OP_RFLOAD) {
#pragma unroll 1
                for (uint32_t tile = (op >> 2) & 6u; tile <= ((op >> 2) | 1u); tile++) {
                    wait_tile(rpos);
#pragma unroll
                    for (int i = 0; i < 8; i++) {
                        if (tile == i) {
#pragma unroll
                            for (int k = 0; k < 6; k++) {
                                if (i & 1) ldsm4t(rf[i][k], frag_addr(rpos, k));
                                else ldsm4(rf[i][k], frag_addr(rpos, k));
                            }
                        }
                    }
                    ring_release();
                }
            } else if (kind == OP_QPROJ) {
                const uint32_t mask = (op >> 3) & 3u;
#pragma unroll 1
                for (uint32_t b = 0; b < 2; b++)
                    if ((mask >> b) & 1u) mbar_wait(sync0 + kBarXn + 8 * b, (op >> 5) & 1u);
                const uint32_t bb = mask == 3u ? (g & 1) : (mask >> 1);
                const uint32_t* xs = reinterpret_cast<const uint32_t*>(smem + kOffXn) + bb * 80 + 4 * w + t;
                float acc[3][4] = {};
#pragma unroll 1
                for (int p = 0; p < 3; p++) {
                    uint32_t xv = xs[p == 2 ? 48 : 32 * p];
                    if (p == 2 && w < 4) xv = 0u;
                    wait_tile(rpos);
#pragma unroll
                    for (int k = 0; k < 6; k++) {
                        uint32_t a[4];
                        ldsm4t(a, frag_addr(rpos, k));
                        mma16816(acc[k >> 1], a, (g >> 1) == 2 * (k & 1) ? xv : 0u, (g >> 1) == 2 * (k & 1) + 1 ? xv : 0u);
                    }
                    ring_release();
                }
#pragma unroll 1
                for (uint32_t b = 0; b < 2; b++) {
                    if (!((mask >> b) & 1u)) continue;
                    row_acquire();
#pragma unroll
                    for (int a = 0; a < 3; a++) {
                        row[64 * a + 16 * t + g] = b ? acc[a][1] : acc[a][0];
                        row[64 * a + 16 * t + g + 8] = b ? acc[a][3] : acc[a][2];
                    }
                    row_publish();
                }
            } else {
                const uint32_t mask = (op >> 3) & 3u;
                const uint32_t bb = mask == 3u ? (g & 1) : (mask >> 1);
                const uint32_t* ob = reinterpret_cast<const uint32_t*>(smem + kOffObf) + bb * 24 + t;
                const uint32_t roff = ((lane & 7) + 8 * (lane >> 4)) * 128 + ((((lane >> 3) & 1) ^ (lane & 7)) << 4);
                const bool ring = !(op >> 8);
                uint32_t sl[3];
#pragma unroll
                for (int p = 0; p < 3; p++) {
                    sl[p] = ring ? rpos : (op >> 8) + p;
                    if (ring && ++rpos == kRing) rpos = 0;
                }
                auto frag = [&](uint32_t (&a)[4], int p, int mt) {
                    ldsm4t(a, ((sbase + sl[p] * 8 * kSlotBytes + roff) ^ (((5 * w + mt) & 3) << 5)) + ((5 * w + mt) >> 2) * 2048);
                };
                uint32_t a0[5][4];
                wait_tile(sl[0]);
#pragma unroll
                for (int mt = 0; mt < 5; mt++) frag(a0[mt], 0, mt);
                if (ring) release(sl[0]);
                wait_tile(sl[1]);
                wait_tile(sl[2]);
                row_acquire();
                if (mask & 1u) mbar_wait(sync0 + kBarO, (op >> 5) & 1u);
                if (mask & 2u) mbar_wait(sync0 + kBarO + 8, (op >> 5) & 1u);
                TRACE_C(0);
                float c[3][4] = {};
#pragma unroll
                for (int p = 0; p < 3; p++) {
                    const uint32_t b0 = ob[8 * p], b1 = ob[8 * p + 4];
#pragma unroll
                    for (int mt = 0; mt < 5; mt++) {
                        if (p > 0) frag(a0[mt], p, mt);
                        const bool on = (g >> 1) == (mt & 3);
                        mma16816(c[mt == 4 ? 2 : (mt & 1)], a0[mt], on ? b0 : 0u, on ? b1 : 0u);
                    }
                    if (p > 0 && ring) release(sl[p]);
                }
                TRACE_C(1);
                row[16 * t + g] = c[0][0] + c[1][0]; row[80 + 16 * t + g] = c[0][1] + c[1][1];
                row[16 * t + g + 8] = c[0][2] + c[1][2]; row[80 + 16 * t + g + 8] = c[0][3] + c[1][3];
                if (t == 0) {
                    row[64 + g] = c[2][0]; row[144 + g] = c[2][1];
                    row[72 + g] = c[2][2]; row[152 + g] = c[2][3];
                }
                __syncwarp();
                if (lane < 27) {
                    const bool last = ((op >> 5) & 3u) == 3u;
                    float4* dst = (last ? g_out[0][cta % kOutReplicas] : g_acc[0][(op >> 5) & 3u]) + 27 * w + lane;
                    const float* y = row + 3 * lane;
                    if (mask & 1u) red_packet(dst, y[0], y[1], lane < 26 ? y[2] : 0.f);
                    if (mask & 2u) red_packet(dst + (last ? kOutReplicas : 3) * kAccPackets, y[80], y[81], lane < 26 ? y[82] : 0.f);
                }
                TRACE_C(3);
                __syncwarp();
                if (lane < 2 && ((mask >> lane) & 1u)) mbar_arrive(sync0 + kBarSentY + 8 * lane);
            }
        }
    } else {
        asm volatile("setmaxnreg.dec.sync.aligned.u32 40;");
        if (w == 8) {
            if (elect()) {
    #pragma unroll
                for (int p = 0; p < kRing; p++) {
                        mbar_expect(sbase + kOffFull + 8 * p, 8 * kSlotBytes);
                    tma3d(sbase + p * 8 * kSlotBytes, &P.tm[4], 0, 160 * jq + (p == 2 ? 96 : 64 * p), 3 * h,
                          sbase + kOffFull + 8 * p, make_policy(false));
                    if (P.keepFirst) tma3d_prefetch(&P.tm[4], 0, 160 * jq + (p == 2 ? 96 : 64 * p), 3 * h, make_policy(true));
                }
            }
            __syncwarp();
            const int rowA = h * 4096 + 3072 + 256 * jq, rowB = h * 4096 + 1024 * jq;
            const int rowWq = 160 * jq, rowWo = 192 * h + 48 * jq;
            const uint32_t tau = P.tau, tauLow = P.tauLow, tauW = P.tauW;
            uint32_t credit = P.credit, na = 0;
            const uint32_t winLow = P.winLow, winHigh = P.winHigh;
            const uint64_t polKeep = make_policy(true), polStream = make_policy(false);
            uint32_t fifo = 0x012u, queued = 7u, stale = 0, par = 7u, nfl = kRing, next = now_ns() + P.startDelay;
            auto coord = [&](uint32_t e) {
                return (int)((e >> 10) & 0x7ffffu) + ((e & 4u) ? ((e & 2u) ? rowWo : rowWq) : ((e & 2u) ? rowB : rowA));
            };
            auto interval = [&](uint32_t e) { return (e & 4u) ? tauW : ((e & LD_LOW) ? tauLow : tau); };
            uint32_t recent = 0x012u;
            auto slot_free = [&](uint32_t s) { return mbar_test(sbase + kOffEmpty + 8 * s, ((par >> s) & 1u) ^ 1u); };
            auto landed = [&](uint32_t s) { return mbar_test(sbase + kOffFull + 8 * s, ((par >> s) & 1u) ^ 1u); };
            auto load = [&](uint32_t e, bool counted) {
                const uint32_t s = (e >> 4) & 15u;
                const int c1 = coord(e), c2 = ((e >> 1) & 3u) == 2u ? 3 * h : 0;
                if (elect()) {
                    mbar_expect(sbase + kOffFull + 8 * s, (e & 6u) == 6u ? 20480 : 8 * kSlotBytes);
                    const bool again = (e & (LD_KEEP | LD_HIT)) == (LD_KEEP | LD_HIT);
                    tma3d(sbase + s * 8 * kSlotBytes, &P.tm[e & 7u], 0, c1, c2, sbase + kOffFull + 8 * s, again ? polKeep : polStream);
                    if ((e & LD_KEEP) && !again) tma3d_prefetch(&P.tm[e & 7u], 0, c1, c2, polKeep);
                }
                if (counted) {
                    fifo = (fifo << 4) | s;
                    queued |= 1u << s;
                    nfl++;
                    recent = (recent << 4) | s;
                }
                par ^= 1u << s;
            };
            uint32_t m = 0, pfd = 0;
#pragma unroll 1
            for (uint32_t n = kRing;; n++) {
                const uint32_t e = P.loads[n];
                if (!(e & LD_VALID)) break;
                const uint32_t s = (e >> 4) & 15u;
                if (m < n) m = n;
                const uint32_t look = (e & LD_FAR) ? P.lookFar : P.look;
                for (uint32_t it = 0; !slot_free(s); it++) {
                    if (it > 16 * kSpinLimit) __trap();
                    const uint32_t f = P.loads[m];
                    if (m >= n + look || !(f & LD_VALID)) continue;
                    if (f & LD_HIT) { m++; continue; }
                    const uint32_t now = now_ns();
                    if ((int)(now - next) >= 0 && landed((recent >> (4 * P.lookBack)) & 15u)) {
                        if (elect()) tma3d_prefetch(&P.tm[f & 7u], 0, coord(f), ((f >> 1) & 3u) == 2u ? 3 * h : 0, polStream);
                        next = now + interval(f);
                        pfd |= 1u << (m & 31u);
                        m++;
                    }
                }
                stale |= queued & (1u << s);
                queued &= ~(1u << s);
                if (e & LD_ANCHOR) {
                    const uint32_t t0 = __shfl_sync(0xffffffffu, *reinterpret_cast<volatile uint32_t*>(smem + kOffAnchor), 0) + P.anchorDelay[na];
                    if (m <= n || (int)(t0 - next) > 0) next = t0;
                    credit = P.anchorCredit[na++];
                }
                const bool counted = !(e & LD_HIT) && !((pfd >> (n & 31u)) & 1u);
                pfd &= ~(1u << (n & 31u));
                if (counted) {
                    for (const uint32_t win = n < P.nStart ? P.winStart : ((e & LD_LOW) ? winLow : winHigh); nfl >= win; nfl--) {
                        const uint32_t o = (fifo >> (4 * nfl - 4)) & 15u;
                        if ((stale >> o) & 1u) {
                            stale ^= 1u << o;
                        } else {
                            mbar_wait_u(sbase + kOffFull + 8 * o, ((par >> o) & 1u) ^ 1u);
                            queued ^= 1u << o;
                        }
                    }
                    uint32_t now = now_ns();
                    while ((int)(now - next) < 0) now = now_ns();
                    if ((int)(now - credit - next) > 0) next = now - credit;
                    next += interval(e);
                }
                load(e, counted);
            }
        } else {
            if (w == 9) {
#pragma unroll 1
                for (int n = 0;; n++) {
                    const uint32_t job = P.merge[n];
                    if ((job & 3u) == MG_END) break;
                    const uint32_t b = (job >> 2) & 1u;
                    const uint32_t tag = 1 + ((job >> 3) & 3u);
                    mbar_wait(sync0 + kBarRows, n & 1);
                    if ((job & 3u) == MG_Q) {
#pragma unroll 1
                        for (int u = lane; u < 40; u += 32) {
                            float o[5] = {};
#pragma unroll
                            for (int i = 0; i < 8; i++)
#pragma unroll
                                for (int k = 0; k < 5; k++) o[k] += wbuf[i * kWRow + 5 * min(u, 38) + k];
                            st_packet5(&g_q[b][h][jq][u], o, tag);
                        }
                        __syncwarp();
                        if (lane == 0) mbar_arrive(sync0 + kBarSentQ + 8 * b);
                    } else {
                        float2* cp = reinterpret_cast<float2*>(smem + kOffCpart) + b * (kWRow / 2) + 3 * lane;
                        float2* cml = reinterpret_cast<float2*>(smem + kOffMl + 64) + b;
                        const float4* ml = reinterpret_cast<const float4*>(smem + kOffMl);
                        const bool merge = !(job & 32u);
                        const float2 pml = merge ? *cml : make_float2(-INFINITY, 0.f);
                        const float4 m0 = ml[0], m1 = ml[1];
                        float sc[8] = {m0.x, m0.y, m0.z, m0.w, m1.x, m1.y, m1.z, m1.w};
                        const float M = fmaxf(fmaxf(fmaxf(fmaxf(sc[0], sc[1]), fmaxf(sc[2], sc[3])),
                                                    fmaxf(fmaxf(sc[4], sc[5]), fmaxf(sc[6], sc[7]))), pml.x);
#pragma unroll
                        for (int i = 0; i < 8; i++) sc[i] = ex2(sc[i] - M);
                        const float ps = ex2(pml.x - M);
                        float2 o[3];
#pragma unroll
                        for (int k = 0; k < 3; k++) {
                            o[k] = merge ? cp[k] : make_float2(0.f, 0.f);
                            o[k].x *= ps; o[k].y *= ps;
                        }
#pragma unroll
                        for (int i = 0; i < 8; i++)
#pragma unroll
                            for (int k = 0; k < 3; k++) {
                                const float2 v = reinterpret_cast<const float2*>(wbuf)[i * (kWRow / 2) + 3 * lane + k];
                                o[k].x = fmaf(v.x, sc[i], o[k].x);
                                o[k].y = fmaf(v.y, sc[i], o[k].y);
                            }
                        const float4 l0 = ml[2], l1 = ml[3];
                        const float L = fmaf(pml.y, ps, ((l0.x * sc[0] + l0.y * sc[1]) + (l0.z * sc[2] + l0.w * sc[3])) +
                                                        ((l1.x * sc[4] + l1.y * sc[5]) + (l1.z * sc[6] + l1.w * sc[7])));
                        if (job & 64u) {
                            uint4* dst = &g_p[b][h][lane >> 3][jq][2 * (lane & 7)];
                            st_packet(dst, o[0].x, o[0].y, o[1].x, tag);
                            st_packet(dst + 1, o[1].y, o[2].x, o[2].y, tag);
                            if (lane < 4) st_packet(&g_p[b][h][lane][jq][16], M, L, 0.f, tag);
                            if (lane == 0) mbar_arrive(sync0 + kBarSentP + 8 * b);
                        } else {
#pragma unroll
                            for (int k = 0; k < 3; k++) cp[k] = o[k];
                            __syncwarp();
                            if (lane == 0) *cml = make_float2(M, L);
                        }
                    }
                    __syncwarp();
                    if (lane == 0) mbar_arrive(sync0 + kBarFree);
                }
            } else {
                const uint32_t b = w - 10;
                __nv_bfloat16* const xn = reinterpret_cast<__nv_bfloat16*>(smem + kOffXn) + b * 160;
                __nv_bfloat16* const qd = reinterpret_cast<__nv_bfloat16*>(smem + kOffQf) + b * 192;
                __nv_bfloat16* const ob = reinterpret_cast<__nv_bfloat16*>(smem + kOffObf) + b * 48;
#pragma unroll 1
                for (uint32_t layer = 0; layer < 4; layer++) {
                    const uint32_t tag = layer + 1;
                    int lane = threadIdx.x & 31;
                    asm volatile("" : "+r"(lane));
                    {
                        uint32_t x01[7], x2[7];
                        if (layer == 0) {
                            const uint4* stage = reinterpret_cast<const uint4*>(wbuf) + 80 * b;
                            asm volatile("cp.async.wait_all;" ::: "memory");
                            __syncwarp();
#pragma unroll
                            for (int i = 0; i < 7; i++) {
                                const int p = lane + 32 * i, u = p % 27;
                                const unsigned short* xp = reinterpret_cast<const unsigned short*>(stage) + (p / 27) * 80 + 3 * u;
                                x01[i] = p < kAccPackets ? xp[0] | ((uint32_t)xp[1] << 16) : 0u;
                                x2[i] = (p < kAccPackets && u < 26) ? xp[2] : 0u;
                            }
                        } else {
                            mbar_wait(sync0 + kBarSentY + 8 * b, (layer - 1) & 1);
                            TRACE_G(4 * layer - 1);
                            uint4 v[7];
                            const uint4* src = reinterpret_cast<const uint4*>(&g_acc[b][layer - 1][lane]);
                            const uint32_t done = __float_as_uint(kAccDone);
                            POLL_UNTIL(SLEEPNS, v[0] = ld_packet(src - lane + 27 * (cta & 7) + min(lane, 26)), v[0].w == done);
                            POLL_UNTIL(SLEEPNS,
                                v[0] = ld_packet(src); v[1] = ld_packet(src + 32); v[2] = ld_packet(src + 64);
                                v[3] = ld_packet(src + 96); v[4] = ld_packet(src + 128); v[5] = ld_packet(src + 160);
                                v[6] = ld_packet(src + (lane < 24 ? 192 : 0)),
                                v[0].w == done && v[1].w == done && v[2].w == done && v[3].w == done && v[4].w == done &&
                                    v[5].w == done && v[6].w == done);
#pragma unroll
                            for (int i = 0; i < 7; i++) {
                                x01[i] = pack_bf16(__uint_as_float(v[i].x), __uint_as_float(v[i].y));
                                x2[i] = pack_bf16(__uint_as_float(v[i].z), 0.f);
                            }
                            if (lane >= 24) x01[6] = x2[6] = 0u;
                        }
                        TRACE_G(16 + 4 * layer);
                        float sum = 0.f;
#pragma unroll
                        for (int i = 0; i < 7; i++) sum += (bf_lo(x01[i]) + bf_hi(x01[i])) + bf_lo(x2[i]);
                        const float mean = warp_sum(sum) * (1.f / 640.f);
                        float sq = 0.f;
#pragma unroll
                        for (int i = 0; i < 7; i++) {
                            const bool none = i == 6 && lane >= 24;
                            const float d0 = none ? 0.f : bf_lo(x01[i]) - mean, d1 = none ? 0.f : bf_hi(x01[i]) - mean;
                            const bool last = lane == 26 - 5 * i || lane == 53 - 5 * i;
                            const float d2 = (none || last) ? 0.f : bf_lo(x2[i]) - mean;
                            sq += fmaf(d0, d0, fmaf(d1, d1, d2 * d2));
                        }
                        const float var = warp_sum(sq) * (1.f / 640.f);
                        const float meanb = bf16r(mean);
                        const float rden = __fdividef(1.f, bf16r(fast_sqrt(bf16r(bf16r(var) + 1e-5f))));
#pragma unroll
                        for (int i = 0; i < 7; i++) {
                            const uint32_t q = lane + 32 * i - 54 * jq;
                            if (q < 54u) {
                                const int c = 3 * q - (q >= 27u);
                                xn[c] = __float2bfloat16_rn(bf16r(bf_lo(x01[i]) - meanb) * rden);
                                xn[c + 1] = __float2bfloat16_rn(bf16r(bf_hi(x01[i]) - meanb) * rden);
                                if (q != 26u && q != 53u) xn[c + 2] = __float2bfloat16_rn(bf16r(bf_lo(x2[i]) - meanb) * rden);
                            }
                        }
                        if (lane == 0) *reinterpret_cast<volatile uint32_t*>(smem + kOffAnchor) = now_ns();
                        __syncwarp();
                        if (lane == 0) mbar_arrive(sync0 + kBarXn + 8 * b);
                        TRACE_G(4 * layer);
#pragma unroll
                        for (int i = 0; i < 7; i++) {
                            const int p = lane + 32 * i;
                            if ((p & 127) == cta && p < kAccPackets) {
                                red_packet((layer == 3 ? g_out[b][0] : g_acc[b][layer]) + p, bf_lo(x01[i]), bf_hi(x01[i]), bf_lo(x2[i]));
                                if (layer >= 2) g_acc[b][layer - 2][p] = make_float4(0.f, 0.f, 0.f, 0.f);
                            }
                        }
                    }
                    {
                        mbar_wait(sync0 + kBarSentQ + 8 * b, layer & 1);
                        uint4 v[5];
                        const uint4* src = &g_q[b][h][0][lane];
                        const uint4* ext = &g_q[b][h][lane & 3][lane < 28 ? 32 + (lane >> 2) : 38];
                        POLL_UNTIL(SLEEPQ,
                            v[0] = ld_packet(src); v[1] = ld_packet(src + 40); v[2] = ld_packet(src + 80);
                            v[3] = ld_packet(src + 120); v[4] = ld_packet(ext),
                            (v[0].w >> 24) == tag && (v[1].w >> 24) == tag && (v[2].w >> 24) == tag &&
                                (v[3].w >> 24) == tag && (v[4].w >> 24) == tag);
                        __syncwarp();
                        TRACE_G(16 + 4 * layer + 1);
                        auto store_q = [&](int d, float q) {
                            qd[(d & ~31) + ((d >> 3) & 1) * 16 + ((d >> 1) & 3) * 4 + ((d >> 4) & 1) * 2 + (d & 1)] =
                                __float2bfloat16_rn(q);
                        };
                        float a[5] = {};
#pragma unroll
                        for (int i = 0; i < 4; i++) add_packet5(a, v[i]);
#pragma unroll
                        for (int k = 0; k < 5; k++) store_q(5 * lane + k, a[k]);
                        float e[5] = {};
                        add_packet5(e, v[4]);
#pragma unroll
                        for (int k = 0; k < 5; k++) {
                            e[k] += __shfl_xor_sync(0xffffffffu, e[k], 1);
                            e[k] += __shfl_xor_sync(0xffffffffu, e[k], 2);
                            const int d = 160 + 5 * (lane >> 2) + k;
                            if ((lane & 3) == 0 && d < 192) store_q(d, e[k]);
                        }
                        __syncwarp();
                        if (lane == 0) mbar_arrive(sync0 + kBarQ + 8 * b);
                        TRACE_G(4 * layer + 1);
                    }
                    if (P.exp) break;
                    {
                        mbar_wait(sync0 + kBarSentP + 8 * b, layer & 1);
                        uint4 v0, v1, ml;
                        const uint4* src = &g_p[b][h][jq][2 * (lane >> 4)][lane & 15];
                        const uint4* mls = &g_p[b][h][jq][lane & 3][16];
                        POLL_UNTIL(SLEEPQ, v0 = ld_packet(src); v1 = ld_packet(src + 18); ml = ld_packet(mls),
                                   v0.w == tag && v1.w == tag && ml.w == tag);
                        __syncwarp();
                        TRACE_G(16 + 4 * layer + 2);
                        const float mi = __uint_as_float(ml.x);
                        float M = fmaxf(mi, __shfl_xor_sync(0xffffffffu, mi, 1));
                        M = fmaxf(M, __shfl_xor_sync(0xffffffffu, M, 2));
                        const float sc = ex2(mi - M);
                        float L = __uint_as_float(ml.y) * sc;
                        L += __shfl_xor_sync(0xffffffffu, L, 1);
                        L += __shfl_xor_sync(0xffffffffu, L, 2);
                        const float s0 = __shfl_sync(0xffffffffu, sc, 2 * (lane >> 4));
                        const float s1 = __shfl_sync(0xffffffffu, sc, 2 * (lane >> 4) + 1);
                        float o0 = fmaf(__uint_as_float(v0.x), s0, __uint_as_float(v1.x) * s1);
                        float o1 = fmaf(__uint_as_float(v0.y), s0, __uint_as_float(v1.y) * s1);
                        float o2 = fmaf(__uint_as_float(v0.z), s0, __uint_as_float(v1.z) * s1);
                        o0 += __shfl_xor_sync(0xffffffffu, o0, 16);
                        o1 += __shfl_xor_sync(0xffffffffu, o1, 16);
                        o2 += __shfl_xor_sync(0xffffffffu, o2, 16);
                        if (lane < 16) {
                            ob[3 * lane] = __float2bfloat16_rn(__fdividef(o0, L));
                            ob[3 * lane + 1] = __float2bfloat16_rn(__fdividef(o1, L));
                            ob[3 * lane + 2] = __float2bfloat16_rn(__fdividef(o2, L));
                        }
                        __syncwarp();
                        if (lane == 0) mbar_arrive(sync0 + kBarO + 8 * b);
                        TRACE_G(4 * layer + 2);
                    }
                }
                if (!P.exp) {
                    mbar_wait(sync0 + kBarSentY + 8 * b, 1);
                    const int p = cta + 128 * ((lane >> 3) & 1), r = lane & 7;
                    float4* src = &g_out[b][r][p < kAccPackets ? p : cta];
                    const float want = kCtas / kOutReplicas + (r == 0);
                    uint4 v;
                    for (uint32_t it = 0;; it++) {
                        v = ld_packet(reinterpret_cast<const uint4*>(src));
                        if (__all_sync(0xffffffffu, v.w == __float_as_uint(want))) break;
                        if (it > kSpinLimit) __trap();
                    }
                    float o0 = __uint_as_float(v.x), o1 = __uint_as_float(v.y), o2 = __uint_as_float(v.z);
#pragma unroll
                    for (int o = 1; o < 8; o <<= 1) {
                        o0 += __shfl_xor_sync(0xffffffffu, o0, o);
                        o1 += __shfl_xor_sync(0xffffffffu, o1, o);
                        o2 += __shfl_xor_sync(0xffffffffu, o2, o);
                    }
                    if (lane < 16 && p < kAccPackets) {
                        if (r < 3 - (p % 27 == 26))
                            P.out[b * 640 + (p / 27) * 80 + 3 * (p % 27) + r] = __float2bfloat16_rn(r == 0 ? o0 : r == 1 ? o1 : o2);
                        *src = make_float4(0.f, 0.f, 0.f, 0.f);
                        if (r == 0) g_acc[b][2][p] = make_float4(0.f, 0.f, 0.f, 0.f);
                    }
                    TRACE_G(15);
                }
            }
        }
    }
}

struct Sched {
    Params& P;
    int np = 0, nm = 0, nl = 0, rslot = 0, mark = 0, lateRet = 0;
    uint32_t pending = 0;
    enum { RF = 1 << 7, FIRST = 1 << 11, PUB = 1 << 12 };
    void low_begin(int back) { mark = nl - back; }
    void low_end(int back) { for (int i = mark; i < nl - back; i++) P.loads[i] |= LD_LOW; }
    void slot(uint32_t e, int s) { P.loads[nl++] = e | (s << 4); }
    void ring(uint32_t e) {
        slot(e | pending, rslot);
        pending = 0;
        rslot = (rslot + 1) % kRing;
    }
    static uint32_t tile(int isB, int b, int idx, int v) {
        return LD_VALID | (2 * isB + v) | (uint32_t)(b * 32 * 4096 + 64 * idx) << 10;
    }
    static uint32_t wq(int layer, int p) { return LD_VALID | (4 + (layer & 1)) | (p == 2 ? 96 : 64 * p) << 10; }
    static uint32_t wo(int layer, int p) { return LD_VALID | (6 + (layer & 1)) | (16 * p) << 10; }
    void kv(int isB, int b, int idx, uint32_t fk = 0, uint32_t fv = 0) {
        ring(tile(isB, b, idx, 0) | fk);
        ring(tile(isB, b, idx, 1) | fv);
    }
    void ret(int b, int idx, int pair) {
        slot(tile(1, b, idx, 0), kRing + 2 * pair);
        slot(tile(1, b, idx, 1), kRing + 2 * pair + 1);
    }
    const char* wuse = "";
    uint32_t wflags() {
        const char c = *wuse ? *wuse++ : '-';
        return ((c == 'k' || c == 'b') ? LD_KEEP : 0u) | ((c == 'h' || c == 'b') ? LD_HIT : 0u);
    }
    void qproj(int mask, int layer, uint32_t f = 0, bool anchor = true) {
        f |= wflags();
        for (int p = 0; p < 3; p++) ring(wq(layer, p) | f);
        if (anchor) pending = LD_ANCHOR;
        P.prog[np++] = OP_QPROJ | (mask << 3) | (layer << 5);
        for (int b = 0; b < 2; b++)
            if ((mask >> b) & 1) P.merge[nm++] = MG_Q | (b << 2) | (layer << 3);
    }
    void oproj(int mask, int layer, uint32_t f = 0, int firstSlot = 0) {
        f |= wflags();
        if (!firstSlot) for (int p = 0; p < 3; p++) ring(wo(layer, p) | f);
        P.prog[np++] = OP_OPROJ | (mask << 3) | (layer << 5) | (firstSlot << 8);
    }
    void rfload(int pair, int isB, int b, int idx) {
        kv(isB, b, idx);
        P.prog[np++] = OP_RFLOAD | (pair << 3);
    }
    void seg(int b, int layer, uint32_t flags, const char* order, int nrel = 0) {
        uint64_t list = 0;
        int nr = 0;
        for (int n = 0; order[n]; n++) {
            const char c = order[n];
            uint64_t it = 12;
            if (c == 'r') { it = 8 | (nr < nrel ? 4 : 0) | (nr % 3 + 1); nr++; }
            else if (c >= 'a' && c <= 'c') it = 12 | (c - 'a' + 1);
            else if (c >= 'A' && c <= 'C') it = 8 | (c - 'A' + 1);
            list |= it << (4 * n);
        }
        P.prog[np++] = OP_SEG | (b << 3) | ((layer & 1) << 4) | (flags & RF);
        P.prog[np++] = (uint32_t)list;
        P.prog[np++] = (uint32_t)(list >> 32);
        P.merge[nm++] = MG_ATTN | (b << 2) | (layer << 3) | ((flags & FIRST) ? 32 : 0) | ((flags & PUB) ? 64 : 0);
    }
    void seg(int b, int layer, uint32_t flags, int nring) { seg(b, layer, flags, &"dddddddddddddddd"[16 - nring]); }
};

const char* tune_str(const char* name, const char* dflt) {
    (void)name;
    return dflt;
}

int tune(const char* name, int dflt) {
    (void)name;
    return dflt;
}

void build_schedule(Params& P) {
    for (int i = 0; i < kMaxProg; i++) P.prog[i] = P.merge[i] = 0;
    for (int i = 0; i < kMaxLoads; i++) P.loads[i] = LD_NONE;
    P.winLow = tune("WINLOW", 3);
    P.winHigh = tune("WINHIGH", 3);
    P.tau = tune("TAU", 965);
    P.tauLow = tune("TAULOW", 1010);
    P.tauW = tune("TAUW", P.tauLow * 5 / 6);
    P.credit = tune("CREDIT", 700);
    for (int i = 0; i < 6; i++) {
        const char dn[4] = {'A', 'D', (char)('0' + i), 0}, cn[4] = {'A', 'C', (char)('0' + i), 0};
        P.anchorDelay[i] = tune(dn, tune("ADELAY", 200));
        P.anchorCredit[i] = tune(cn, i == 0 ? 2500 : i == 1 ? 1500 : P.credit);
    }
    P.startDelay = tune("STARTDELAY", 1000);
    P.look = tune("LOOK", 4);
    P.lookBack = tune("LOOKBACK", 0);
    P.nStart = tune("NSTART", 10);
    P.winStart = tune("WINSTART", 4);
    P.lookFar = tune("LOOKFAR", 4);

    Sched S{P};
    using F = Sched;
    S.wuse = tune_str("WK", "k-k-h-h-----");
    const int keep[2] = {tune("KEEP0", 9), tune("KEEP1", 10)};
    auto flag = [&](int b, int idx, int v, uint32_t f) { return (2 * (15 - idx) + (1 - v)) < keep[b] ? f : 0u; };
    const int hit[2] = {16 - (keep[0] + 1) / 2, 16 - (keep[1] + 1) / 2};
    int next0 = 3, next1 = 7, nextA = 0;
    auto first0 = [&](const char* order, uint32_t flags) {
        for (const char* c = order; *c; c++)
            if (*c != 'r') {
                S.kv(1, 0, next0, flag(0, next0, 0, LD_KEEP), flag(0, next0, 1, LD_KEEP));
                if (++next0 == 5) for (; S.lateRet > 0; S.lateRet--) S.ret(0, 3 - S.lateRet, 3 - S.lateRet);
            }
        S.seg(0, 1, flags, order);
    };
    auto fillA = [&](const char* order, uint32_t flags) {
        int nr = 0;
        for (const char* c = order; *c; c++) if (*c == 'r') nr++; else S.kv(0, 1, nextA++);
        S.seg(1, 0, flags, order, nr);
    };
    auto fill0 = [&](int n, uint32_t flags = 0) {
        int c = 0;
        for (; c < n && next0 < hit[0]; c++) S.kv(1, 0, next0++);
        if (c > 0 || flags) S.seg(0, 3, flags, c);
    };
    auto fill1 = [&](int n) {
        int c = 0;
        const uint32_t flags = next1 == 7 ? F::FIRST : 0;
        for (; c < n && next1 < hit[1]; c++) S.kv(1, 1, next1++);
        if (c > 0) S.seg(1, 1, flags, c);
    };
    int nextH[2] = {hit[0], hit[1]}, nextK = hit[1], nextD1 = 10;
    bool started[2] = {};
    auto phase = [&](const char* spec, const int (&layer)[2], int refill0, const char* pos, int pubMask) {
        int tiles = 0, nq = 0, done = 0, due[8] = {};
        uint32_t ent[8] = {};
        auto flush = [&](int upto) { while (done < nq && due[done] <= upto) P.loads[S.nl++] = ent[done++]; };
        for (const char* c = spec; *c; c++) {
            if (!nq && (*c == 'h' || *c == 'd' || *c == 'k')) tiles += 2;
            if (*c >= 'a' && *c <= 'c')
                for (int v = 0; v < 2; v++, nq++) {
                    due[nq] = tiles + (pos[nq] <= '9' ? pos[nq] - '0' : pos[nq] - 'a' + 10);
                    ent[nq] = F::tile(1, 1, refill0 + nq / 2, v) | LD_FAR | ((kRing + 2 * (*c - 'a') + v) << 4);
                }
        }
        tiles = 0;
        for (const char* c = spec; *c;) {
            const int b = *c++ - '0';
            char order[20];
            int n = 0;
            uint32_t flags = started[b] ? 0 : F::FIRST;
            started[b] = true;
            for (; *c && *c != '.'; c++) {
                if (*c == 'R') { flags |= F::RF; continue; }
                order[n++] = *c;
                if (*c != 'h' && *c != 'd' && *c != 'k') continue;
                const int idx = *c == 'h' ? nextH[b]++ : *c == 'k' ? nextK++ : b ? nextD1++ : next0++;
                for (int v = 0; v < 2; v++, tiles++) {
                    flush(tiles);
                    S.ring(F::tile(1, b, idx, v) | LD_FAR | flag(b, idx, v, *c == 'h' ? LD_HIT : *c == 'k' ? LD_KEEP : 0));
                }
            }
            order[n] = 0;
            bool last = true;
            for (const char* r = c; *r; r++) if (*r == '.' && r[1] - '0' == b) last = false;
            S.seg(b, layer[b], flags | ((last && ((pubMask >> b) & 1)) ? F::PUB : 0), order);
            if (*c) c++;
        }
        flush(1 << 20);
    };

    P.keepFirst = 0;

    P.exp = tune("EXP", 0);
    if (P.exp) {
        S.qproj(3, 0);
        for (int r = 0; r < 2; r++)
            for (int b = 0; b < 2; b++) {
                for (int i = 0; i < 15; i++) S.kv(1, b, i);
                S.seg(b, 0, F::FIRST, 15);
            }
        return;
    }
    const int lb = tune("LOWBACK", 0);
    const int early = tune("EARLY", 1);
    S.qproj(3, 0, 0, false);
    P.keepFirst = P.loads[0] & LD_KEEP;
    for (int i = 0; i < early; i++) {
        S.slot(F::tile(0, 1, i, 0), kRing + 2 * i);
        S.slot(F::tile(0, 1, i, 1), kRing + 2 * i + 1);
    }
    for (int i = 0; i < 4; i++) S.rfload(i, 0, 0, i);
    S.seg(0, 0, F::RF | F::FIRST | F::PUB, 0);
    S.low_begin(lb);
    if (tune("JOINT", 1)) {
        nextA = early;
        fillA(tune_str("LA", "rddd"), F::FIRST | F::PUB);
        const int late = tune("RETLATE", 0);
        S.oproj(3, 0);
        for (int i = 0; i < 3 - late; i++) S.ret(0, i, i);
        S.qproj(3, 1);
        S.low_end(0);
        S.lateRet = late;
        first0(tune_str("L2", "dddrdddrdddrdddd"), F::FIRST | F::PUB);
    } else {
        nextA = early;
        fillA(tune_str("LA1", "d"), F::FIRST);
        S.oproj(1, 0, LD_KEEP);
        fillA(tune_str("LA2", "ddd"), F::PUB);
        S.qproj(1, 1, LD_KEEP);
        S.pending = 0;
        P.loads[S.nl] = 0;
        S.ret(0, 0, 0);
        P.loads[S.nl - 2] |= tune("RETANCHOR", 0) ? LD_ANCHOR : 0;
        S.oproj(2, 0, LD_HIT);
        S.ret(0, 1, 1);
        S.ret(0, 2, 2);
        first0(tune_str("L2A", "ddd"), F::FIRST);
        S.qproj(2, 1, LD_HIT);
        S.low_end(0);
        first0(tune_str("L2B", "drddrddrddddd"), F::PUB);
    }
    next0 = 3;
    S.low_begin(lb);
    fill1(tune("F21", 0));
    S.oproj(1, 1);
    fill1(tune("F22", 2));
    S.qproj(1, 2);
    fill1(tune("F23", 1));
    S.seg(0, 2, F::RF | F::FIRST | F::PUB, 0);
    const int r1 = tune("R31", 1), r2 = r1 + tune("R32", 2);
    for (int i = 0; i < r1; i++) S.rfload(i, 1, 1, 3 + i);
    fill1(tune("F31", 0));
    S.oproj(1, 2);
    for (int i = r1; i < r2; i++) S.rfload(i, 1, 1, 3 + i);
    fill1(tune("F32", 1));
    S.qproj(1, 3);
    for (int i = r2; i < 4; i++) S.rfload(i, 1, 1, 3 + i);
    fill1(16);
    S.low_end(0);
    started[1] = next1 > 7;
    phase(tune_str("P4", "0ahbchhhh.1RkkkAkBCk"), {3, 1}, 0, tune_str("POS4", "334577"), 2);
    S.low_begin(lb);
    fill0(tune("F41", 0));
    S.oproj(2, 1);
    fill0(tune("F42", 2));
    S.qproj(2, 2);
    fill0(tune("F43", 1));
    for (int i = 0; i < 4; i++) S.kv(0, 1, i);
    S.seg(1, 2, F::FIRST | F::PUB, 4);
    fill0(tune("F51", 1));
    S.oproj(2, 2);
    fill0(tune("F52", 2));
    S.qproj(2, 3);
    fill0(tune("F53", 0));
    S.low_end(0);
    started[1] = false;
    phase(tune_str("P6", "0dd.1RabdchhhAhBhC"), {3, 3}, 7, tune_str("POS6", "33579b"), 3);
    S.oproj(3, 3);
}

typedef CUresult (*EncodeFn)(CUtensorMap*, CUtensorMapDataType, cuuint32_t, void*, const cuuint64_t*,
                             const cuuint64_t*, const cuuint32_t*, const cuuint32_t*, CUtensorMapInterleave,
                             CUtensorMapSwizzle, CUtensorMapL2promotion, CUtensorMapFloatOOBfill);

}

extern "C" void kernel_launch(void* const* d_in, const int* in_sizes, int n_in, void* d_out, int out_size) {
    (void)in_sizes; (void)n_in; (void)out_size;
    Params P;
    void* fn = nullptr;
    cudaDriverEntryPointQueryResult qr;
    cudaGetDriverEntryPoint("cuTensorMapEncodeTiled", &fn, cudaEnableDefault, &qr);
    EncodeFn encode = reinterpret_cast<EncodeFn>(fn);
    const CUtensorMapL2promotion promo = (CUtensorMapL2promotion)tune("PROMO", CU_TENSOR_MAP_L2_PROMOTION_NONE);
    void* kv[4] = {d_in[1], d_in[2], d_in[6], d_in[7]};
    for (int i = 0; i < 4; i++) {
        const cuuint64_t dims[3] = {64, 2ull * 32 * 4096, 3};
        const cuuint64_t strides[2] = {384, 128};
        const cuuint32_t box[3] = {64, 64, 3};
        const cuuint32_t es[3] = {1, 1, 1};
        encode(&P.tm[i], CU_TENSOR_MAP_DATA_TYPE_BFLOAT16, 3, kv[i], dims, strides, box, es,
               CU_TENSOR_MAP_INTERLEAVE_NONE, CU_TENSOR_MAP_SWIZZLE_128B, promo, CU_TENSOR_MAP_FLOAT_OOB_FILL_NONE);
    }
    void* wq[2] = {d_in[3], d_in[8]};
    for (int i = 0; i < 2; i++) {
        const cuuint64_t dims[3] = {64, 640, 96};
        const cuuint64_t strides[2] = {12288, 128};
        const cuuint32_t box[3] = {64, 64, 3};
        const cuuint32_t es[3] = {1, 1, 1};
        encode(&P.tm[4 + i], CU_TENSOR_MAP_DATA_TYPE_BFLOAT16, 3, wq[i], dims, strides, box, es,
               CU_TENSOR_MAP_INTERLEAVE_NONE, CU_TENSOR_MAP_SWIZZLE_128B, promo, CU_TENSOR_MAP_FLOAT_OOB_FILL_NONE);
    }
    void* wo[2] = {d_in[4], d_in[9]};
    for (int i = 0; i < 2; i++) {
        const cuuint64_t dims[3] = {64, 6144, 10};
        const cuuint64_t strides[2] = {1280, 128};
        const cuuint32_t box[3] = {64, 16, 10};
        const cuuint32_t es[3] = {1, 1, 1};
        encode(&P.tm[6 + i], CU_TENSOR_MAP_DATA_TYPE_BFLOAT16, 3, wo[i], dims, strides, box, es,
               CU_TENSOR_MAP_INTERLEAVE_NONE, CU_TENSOR_MAP_SWIZZLE_128B, promo, CU_TENSOR_MAP_FLOAT_OOB_FILL_NONE);
    }
    P.x = static_cast<const __nv_bfloat16*>(d_in[0]);
    P.out = static_cast<__nv_bfloat16*>(d_out);
    build_schedule(P);
    cudaFuncSetAttribute(fused_decode_kernel, cudaFuncAttributeMaxDynamicSharedMemorySize, kSmemBytes);
    fused_decode_kernel<<<kCtas, kThreads, kSmemBytes>>>(P);
}
```

```cpp
#include <cuda_runtime.h>
#include <cuda_bf16.h>
#include <cuda.h>
#include <stdint.h>

namespace {

constexpr int kCtas = 128;
constexpr int kThreads = 384;
constexpr int kSlotBytes = 3072;
constexpr int kRing = 3;
constexpr int kSlots = 9;
constexpr int kWRow = 192;

constexpr int kOffWbuf = kSlots * 8 * kSlotBytes;
constexpr int kOffMl = kOffWbuf + 8 * kWRow * 4;
constexpr int kOffCpart = kOffMl + 20 * 4;
constexpr int kOffQf = kOffCpart + 2 * kWRow * 4;
constexpr int kOffXn = kOffQf + 2 * 96 * 4;
constexpr int kOffObf = kOffXn + 2 * 160 * 2;
constexpr int kOffFull = kOffObf + 2 * 48 * 2;
constexpr int kOffEmpty = kOffFull + kSlots * 8;
constexpr int kOffSync = kOffEmpty + kSlots * 8;
constexpr int kOffAnchor = kOffSync + 14 * 8;
constexpr int kOffOwn = kOffAnchor + 8;
constexpr int kSmemBytes = kOffOwn + 32;
static_assert(kSmemBytes <= 232448, "shared memory budget");
constexpr int kBarRows = 0, kBarFree = 8, kBarQ = 16, kBarXn = 32, kBarO = 48;
constexpr int kBarSentQ = 64, kBarSentP = 80, kBarSentY = 96;

constexpr int kMaxProg = 112;
constexpr int kMaxLoads = 200;

enum : uint32_t { OP_END = 0, OP_QPROJ = 1, OP_RFLOAD = 2, OP_SEG = 3, OP_OPROJ = 4 };
enum : uint32_t { LD_NONE = 0, LD_KEEP = 1u << 3, LD_LOW = 1u << 8, LD_VALID = 1u << 9, LD_ANCHOR = 1u << 29, LD_FAR = 1u << 30, LD_HIT = 1u << 31 };
enum : uint32_t { MG_END = 0, MG_ATTN = 1, MG_Q = 2 };

struct alignas(64) Params {
    CUtensorMap tm[8];
    const __nv_bfloat16* x;
    __nv_bfloat16* out;
    uint32_t winLow, winHigh;
    uint32_t tau, tauLow, tauW, credit;
    uint32_t look, lookBack, lookFar, nStart, winStart;
    uint32_t anchorDelay[6], anchorCredit[6], startDelay, keepFirst, qDelay, xDelay, qDelay2, pDelay;
    uint32_t exp;
    uint32_t prog[kMaxProg];
    uint32_t merge[kMaxProg];
    uint32_t loads[kMaxLoads];
};

__device__ uint4 g_q[2][32][4][40];
__device__ uint4 g_p[2][32][4][4][18];
constexpr int kAccPackets = 216;
constexpr float kAccDone = 129.f;
#define ACCPAD 2
constexpr int kAccPad = ACCPAD;
__device__ float4 g_acc[2][3][kAccPackets * kAccPad];
constexpr int kOutReplicas = 8;
__device__ float4 g_out[2][kOutReplicas][kAccPackets];

#define SLEEPNS 200
#define PSLEEP 0
#define SLEEPQ 0
constexpr uint32_t kSpinLimit = 1u << 22;

__device__ __forceinline__ void mbar_init(uint32_t bar, uint32_t count) {
    asm volatile("mbarrier.init.shared::cta.b64 [%0], %1;" ::"r"(bar), "r"(count) : "memory");
}
__device__ __forceinline__ void mbar_arrive(uint32_t bar) {
    asm volatile("mbarrier.arrive.shared::cta.b64 _, [%0];" ::"r"(bar) : "memory");
}
__device__ __forceinline__ bool mbar_test(uint32_t bar, uint32_t parity) {
    uint32_t ok;
    asm volatile(
        "{\n\t.reg .pred p;\n\t"
        "mbarrier.test_wait.parity.shared::cta.b64 p, [%1], %2;\n\t"
        "selp.u32 %0, 1, 0, p;\n\t}"
        : "=r"(ok) : "r"(bar), "r"(parity) : "memory");
    return __all_sync(0xffffffffu, ok);
}
__device__ __forceinline__ void mbar_expect(uint32_t bar, uint32_t bytes) {
    asm volatile("mbarrier.arrive.expect_tx.shared::cta.b64 _, [%0], %1;" ::"r"(bar), "r"(bytes) : "memory");
}
__device__ __forceinline__ void mbar_wait(uint32_t bar, uint32_t parity) {
    uint32_t ok, it = 0;
    do {
        asm volatile(
            "{\n\t.reg .pred p;\n\t"
            "mbarrier.try_wait.parity.shared::cta.b64 p, [%1], %2;\n\t"
            "selp.u32 %0, 1, 0, p;\n\t}"
            : "=r"(ok) : "r"(bar), "r"(parity) : "memory");
        if (++it > kSpinLimit) __trap();
    } while (!ok);
}
__device__ __forceinline__ bool mbar_try(uint32_t bar, uint32_t parity) {
    uint32_t ok;
    asm volatile(
        "{\n\t.reg .pred p;\n\t"
        "mbarrier.try_wait.parity.shared::cta.b64 p, [%1], %2;\n\t"
        "selp.u32 %0, 1, 0, p;\n\t}"
        : "=r"(ok) : "r"(bar), "r"(parity) : "memory");
    return __all_sync(0xffffffffu, ok);
}
__device__ __forceinline__ void mbar_wait_u(uint32_t bar, uint32_t parity) {
    for (uint32_t it = 0; !mbar_try(bar, parity); it++)
        if (it > kSpinLimit) __trap();
}
__device__ __forceinline__ void prefetch_l2(const void* p) {
    asm volatile("prefetch.global.L2 [%0];" ::"l"(p) : "memory");
}
__device__ __forceinline__ void tma3d(uint32_t dst, const CUtensorMap* tm, int c0, int c1, int c2, uint32_t bar, uint64_t pol) {
    asm volatile(
        "cp.async.bulk.tensor.3d.shared::cluster.global.mbarrier::complete_tx::bytes.L2::cache_hint "
        "[%0], [%1, {%2, %3, %4}], [%5], %6;"
        ::"r"(dst), "l"(tm), "r"(c0), "r"(c1), "r"(c2), "r"(bar), "l"(pol) : "memory");
}
__device__ __forceinline__ void tma3d_prefetch(const CUtensorMap* tm, int c0, int c1, int c2, uint64_t pol) {
    asm volatile("cp.async.bulk.prefetch.tensor.3d.L2.global.L2::cache_hint [%0, {%1, %2, %3}], %4;"
                 ::"l"(tm), "r"(c0), "r"(c1), "r"(c2), "l"(pol) : "memory");
}
__device__ __forceinline__ uint64_t make_policy(bool keep) {
    uint64_t pol;
    if (keep) asm volatile("createpolicy.fractional.L2::evict_normal.b64 %0, 1.0;" : "=l"(pol));
    else      asm volatile("createpolicy.fractional.L2::evict_first.b64 %0, 1.0;" : "=l"(pol));
    return pol;
}
__device__ __forceinline__ void ldsm4(uint32_t (&r)[4], uint32_t addr) {
    asm volatile("ldmatrix.sync.aligned.m8n8.x4.shared.b16 {%0,%1,%2,%3}, [%4];"
                 : "=r"(r[0]), "=r"(r[1]), "=r"(r[2]), "=r"(r[3]) : "r"(addr) : "memory");
}
__device__ __forceinline__ void ldsm4t(uint32_t (&r)[4], uint32_t addr) {
    asm volatile("ldmatrix.sync.aligned.m8n8.x4.trans.shared.b16 {%0,%1,%2,%3}, [%4];"
                 : "=r"(r[0]), "=r"(r[1]), "=r"(r[2]), "=r"(r[3]) : "r"(addr) : "memory");
}
__device__ __forceinline__ void mma16816(float (&c)[4], const uint32_t (&a)[4], uint32_t b0, uint32_t b1) {
    asm volatile("mma.sync.aligned.m16n8k16.row.col.f32.bf16.bf16.f32 {%0,%1,%2,%3}, {%4,%5,%6,%7}, {%8,%9}, {%0,%1,%2,%3};"
                 : "+f"(c[0]), "+f"(c[1]), "+f"(c[2]), "+f"(c[3])
                 : "r"(a[0]), "r"(a[1]), "r"(a[2]), "r"(a[3]), "r"(b0), "r"(b1));
}
__device__ __forceinline__ float bf16r(float v) { return __bfloat162float(__float2bfloat16_rn(v)); }
__device__ __forceinline__ uint32_t pack_bf16(float lo, float hi) {
    uint32_t r;
    asm("cvt.rn.bf16x2.f32 %0, %1, %2;" : "=r"(r) : "f"(hi), "f"(lo));
    return r;
}
__device__ __forceinline__ bool elect() {
    uint32_t p;
    asm volatile("{\n\t.reg .pred e;\n\telect.sync _|e, 0xffffffff;\n\tselp.u32 %0, 1, 0, e;\n\t}" : "=r"(p));
    return p;
}
__device__ __forceinline__ float fast_sqrt(float v) {
    float r;
    asm("sqrt.approx.f32 %0, %1;" : "=f"(r) : "f"(v));
    return r;
}
__device__ __forceinline__ float ex2(float v) {
    float r;
    asm("ex2.approx.ftz.f32 %0, %1;" : "=f"(r) : "f"(v));
    return r;
}
__device__ __forceinline__ void st_packet(uint4* p, uint32_t a, uint32_t b, uint32_t c, uint32_t tag) {
    asm volatile(
        "{\n\t.reg .b64 lo, hi;\n\t.reg .b128 v;\n\t"
        "mov.b64 lo, {%1, %2};\n\tmov.b64 hi, {%3, %4};\n\tmov.b128 v, {lo, hi};\n\t"
        "st.relaxed.gpu.global.b128 [%0], v;\n\t}"
        ::"l"(p), "r"(a), "r"(b), "r"(c), "r"(tag) : "memory");
}
__device__ __forceinline__ void st_packet(uint4* p, float a, float b, float c, uint32_t tag) {
    st_packet(p, __float_as_uint(a), __float_as_uint(b), __float_as_uint(c), tag);
}
__device__ __forceinline__ uint4 ld_packet(const uint4* p) {
    uint4 v;
    asm volatile(
        "{\n\t.reg .b64 lo, hi;\n\t.reg .b128 v;\n\t"
        "ld.relaxed.gpu.global.b128 v, [%4];\n\t"
        "mov.b128 {lo, hi}, v;\n\tmov.b64 {%0, %1}, lo;\n\tmov.b64 {%2, %3}, hi;\n\t}"
        : "=r"(v.x), "=r"(v.y), "=r"(v.z), "=r"(v.w) : "l"(p) : "memory");
    return v;
}
__device__ __forceinline__ void red_packet(float4* p, float a, float b, float c) {
    asm volatile("red.relaxed.gpu.global.add.v4.f32 [%0], {%1, %2, %3, %4};"
                 ::"l"(p), "f"(a), "f"(b), "f"(c), "f"(1.f) : "memory");
}
#define POLL_UNTIL(pause, loads, done)            \
    for (uint32_t it_ = 0;; it_++) {              \
        loads;                                    \
        if (__all_sync(0xffffffffu, done)) break; \
        if (it_ > kSpinLimit) __trap();           \
        if (pause) __nanosleep(pause);            \
    }
__device__ __forceinline__ uint32_t round24(float v) {
    const uint32_t u = __float_as_uint(v);
    return u + ((u & 0x7f800000u) == 0x7f800000u ? 0u : 0x80u);
}
__device__ __forceinline__ void st_packet5(uint4* p, const float* v, uint32_t tag) {
    const uint32_t r0 = round24(v[0]), r1 = round24(v[1]), r2 = round24(v[2]), r3 = round24(v[3]), r4 = round24(v[4]);
    st_packet(p, __byte_perm(r0, r1, 0x5321), __byte_perm(r1, r2, 0x6532), __byte_perm(r2, r3, 0x7653),
              (r4 >> 8) | (tag << 24));
}
__device__ __forceinline__ void add_packet5(float (&a)[5], const uint4& v) {
    a[0] += __uint_as_float(v.x << 8);
    a[1] += __uint_as_float(__funnelshift_r(v.x, v.y, 16) & 0xffffff00u);
    a[2] += __uint_as_float(__funnelshift_r(v.y, v.z, 8) & 0xffffff00u);
    a[3] += __uint_as_float(v.z & 0xffffff00u);
    a[4] += __uint_as_float(v.w << 8);
}
__device__ __forceinline__ uint32_t now_ns() {
    uint32_t t;
    asm volatile("mov.u32 %0, %globaltimer_lo;" : "=r"(t));
    return t;
}
__device__ __forceinline__ int fresh_lane() {
    int lane = threadIdx.x & 31;
    asm volatile("" : "+r"(lane));
    return lane;
}
__device__ __forceinline__ void pause_ns(uint32_t ns) {
    const uint32_t t0 = now_ns();
    while (now_ns() - t0 < ns) __nanosleep(100);
}
__device__ __forceinline__ float bf_lo(uint32_t v) { return __uint_as_float(v << 16); }
__device__ __forceinline__ float bf_hi(uint32_t v) { return __uint_as_float(v & 0xffff0000u); }
__device__ __forceinline__ float warp_sum(float v) {
#pragma unroll
    for (int o = 16; o > 0; o >>= 1) v += __shfl_xor_sync(0xffffffffu, v, o);
    return v;
}

constexpr float kScale = 0.07216878364870322f * 1.4426950408889634f;

struct Attn {
    float m, l;
    float acc[3][4];
};

__device__ __forceinline__ uint32_t probability(Attn& st, float s) {
    const float e = ex2(s - st.m);
    st.l += e;
    const float hi = bf16r(e);
    const uint32_t hl = pack_bf16(hi, e - hi);
    uint32_t pv;
    asm volatile("movmatrix.sync.aligned.m8n8.trans.b16 %0, %1;" : "=r"(pv) : "r"(hl));
    return pv;
}

__device__ __forceinline__ uint32_t softmax_step(Attn& st, float s) {
    if (__any_sync(0xffffffffu, s > st.m)) {
        float mx = fmaxf(s, __shfl_xor_sync(0xffffffffu, s, 4));
        mx = fmaxf(mx, __shfl_xor_sync(0xffffffffu, mx, 8));
        mx = fmaxf(mx, __shfl_xor_sync(0xffffffffu, mx, 16));
        mx = fmaxf(mx, st.m);
        const float corr = ex2(st.m - mx);
        st.m = mx;
        st.l *= corr;
#pragma unroll
        for (int a = 0; a < 3; a++)
#pragma unroll
            for (int i = 0; i < 4; i++) st.acc[a][i] *= corr;
    }
    return probability(st, s);
}

#define TRACE_G(i)
#define TRACE_C(i)

__global__ void __launch_bounds__(kThreads, 1)
fused_decode_kernel(const __grid_constant__ Params P) {
    extern __shared__ __align__(1024) unsigned char smem[];
    const uint32_t sbase = (uint32_t)__cvta_generic_to_shared(smem);
    const uint32_t sync0 = sbase + kOffSync;
    float* const wbuf = reinterpret_cast<float*>(smem + kOffWbuf);

    const int lane = threadIdx.x & 31;
    const int w = __shfl_sync(0xffffffffu, threadIdx.x >> 5, 0);
    const int cta = blockIdx.x;
    const int h = cta >> 2, jq = cta & 3;

    if (w >= 10) {
        const int i0 = 80 * (w - 10) + lane;
#pragma unroll
        for (int i = 0; i < 3; i++)
            if (i < 2 || lane < 16)
                asm volatile("cp.async.cg.shared.global [%0], [%1], 16;"
                             ::"r"(sbase + kOffWbuf + 16 * (i0 + 32 * i)), "l"(reinterpret_cast<const uint4*>(P.x) + i0 + 32 * i) : "memory");
    }
    if (elect()) {
        if (w == 8) {
#pragma unroll
            for (int i = 0; i < kSlots; i++) {
                mbar_init(sbase + kOffFull + 8 * i, 1);
                mbar_init(sbase + kOffEmpty + 8 * i, 8);
            }
        } else if (w == 9) {
#pragma unroll
            for (int i = 0; i < 8; i++) asm volatile("prefetch.tensormap [%0];" ::"l"(&P.tm[i]) : "memory");
        } else if (w == 10) {
#pragma unroll
            for (int i = 0; i < 14; i++) mbar_init(sync0 + 8 * i, (8 * i == kBarRows || 8 * i >= kBarSentY) ? 8 : 1);
        }
        if (w != 9) asm volatile("fence.mbarrier_init.release.cluster;" ::: "memory");
    }
    __syncwarp();
    if (w == 8) {
        asm volatile("bar.arrive 1, %0;" ::"n"(kThreads) : "memory");
    } else {
        asm volatile("bar.sync 1, %0;" ::"n"(kThreads) : "memory");
    }

    if (w < 8) {
        asm volatile("setmaxnreg.inc.sync.aligned.u32 232;");
        const uint32_t full0 = sbase + kOffFull;
        const uint32_t frag0 = sbase + w * 1024 + (lane & 7) * 128 + (((lane >> 3) ^ (lane & 7)) << 4), frag1 = frag0 ^ 64;
        auto frag_addr = [&](uint32_t s, int k) { return ((k & 1) ? frag1 : frag0) + s * (8 * kSlotBytes) + (k >> 1) * 8192; };
        uint32_t par = 0, rpos = 0, nrows = 0;
        auto wait_tile = [&](uint32_t s) { mbar_wait(full0 + 8 * s, (par >> s) & 1u); };
        auto tile_ready = [&](uint32_t s) { return mbar_test(full0 + 8 * s, (par >> s) & 1u); };
        auto release = [&](uint32_t s) {
            par ^= 1u << s;
            __syncwarp();
            if (elect()) mbar_arrive(full0 + 8 * s + (kOffEmpty - kOffFull));
        };
        auto ring_release = [&]() {
            release(rpos);
            if (++rpos == kRing) rpos = 0;
        };
        auto row_acquire = [&]() { mbar_wait(sync0 + kBarFree, (nrows & 1) ^ 1); };
        auto row_publish = [&]() {
            __syncwarp();
            if (elect()) mbar_arrive(sync0 + kBarRows);
            nrows++;
        };

        uint32_t rf[8][6][4];
#pragma unroll
        for (int i = 0; i < 8; i++)
#pragma unroll
            for (int s = 0; s < 6; s++)
#pragma unroll
                for (int k = 0; k < 4; k++) rf[i][s][k] = 0;

#pragma unroll 1
        for (int pc = 0;; pc++) {
            const uint32_t op = P.prog[pc];
            const uint32_t kind = op & 7u;
            if (kind == OP_END) break;
            const int lane = fresh_lane();
            const int g = lane >> 2, t = lane & 3;
            float* const row = wbuf + w * kWRow;

            if (kind == OP_SEG) {
                const uint32_t b = (op >> 3) & 1u;
                mbar_wait(sync0 + kBarQ + 8 * b, (op >> 4) & 1u);
                const uint2* qf = reinterpret_cast<const uint2*>(smem + kOffQf) + b * 48 + (lane & 7);
                Attn st;
                st.m = -INFINITY; st.l = 0.f;
#pragma unroll
                for (int a = 0; a < 3; a++)
#pragma unroll
                    for (int i = 0; i < 4; i++) st.acc[a][i] = 0.f;

                if (op & (1u << 7)) {
                    float c[4][4] = {};
#pragma unroll
                    for (int k = 0; k < 6; k++) {
                        const uint2 q = qf[8 * k];
#pragma unroll
                        for (int i = 0; i < 4; i++) mma16816(c[i], rf[2 * i][k], q.x, q.y);
                    }
                    float sc[4];
#pragma unroll
                    for (int i = 0; i < 4; i++) sc[i] = (c[i][0] + c[i][3]) * kScale;
                    float mx = fmaxf(fmaxf(sc[0], sc[1]), fmaxf(sc[2], sc[3]));
                    mx = fmaxf(mx, __shfl_xor_sync(0xffffffffu, mx, 4));
                    mx = fmaxf(mx, __shfl_xor_sync(0xffffffffu, mx, 8));
                    st.m = fmaxf(mx, __shfl_xor_sync(0xffffffffu, mx, 16));
                    uint32_t pv[4];
#pragma unroll
                    for (int i = 0; i < 4; i++) pv[i] = probability(st, sc[i]);
#pragma unroll
                    for (int i = 0; i < 4; i++)
#pragma unroll
                        for (int k = 0; k < 6; k++)
                            mma16816(st.acc[k >> 1], rf[2 * i + 1][k], (g >> 1) == 2 * (k & 1) ? pv[i] : 0u,
                                     (g >> 1) == 2 * (k & 1) + 1 ? pv[i] : 0u);
                }

                uint32_t lo = P.prog[pc + 1], hi = P.prog[pc + 2];
                pc += 2;
                bool haveK = false;
#pragma unroll 1
                while (lo & 15u) {
                    const bool rel = lo & 4u;
                    uint32_t sK = kRing - 2 + 2 * (lo & 3u), sV = sK + 1;
                    if (!(lo & 3u)) {
                        sK = rpos;
                        sV = rpos == kRing - 1 ? 0 : rpos + 1;
                        rpos = sV == kRing - 1 ? 0 : sV + 1;
                    }
                    lo = __funnelshift_r(lo, hi, 4);
                    hi >>= 4;
                    if (!haveK) wait_tile(sK);
                    const bool haveV = tile_ready(sV);
                    float c[2][4] = {};
#pragma unroll
                    for (int k = 0; k < 6; k++) {
                        uint32_t a[4];
                        ldsm4(a, frag_addr(sK, k));
                        const uint2 q = qf[8 * k];
                        mma16816(c[k & 1], a, q.x, q.y);
                    }
                    if (rel) release(sK);
                    const uint32_t pv = softmax_step(st, ((c[0][0] + c[0][3]) + (c[1][0] + c[1][3])) * kScale);
                    if (!haveV) wait_tile(sV);
                    haveK = tile_ready((lo & 3u) ? kRing - 2 + 2 * (lo & 3u) : rpos);
#pragma unroll
                    for (int k = 0; k < 6; k++) {
                        uint32_t a[4];
                        ldsm4t(a, frag_addr(sV, k));
                        mma16816(st.acc[k >> 1], a, (g >> 1) == 2 * (k & 1) ? pv : 0u, (g >> 1) == 2 * (k & 1) + 1 ? pv : 0u);
                    }
                    if (rel) release(sV);
                }

                TRACE_C(4);
                float l = st.l;
                l += __shfl_xor_sync(0xffffffffu, l, 4);
                l += __shfl_xor_sync(0xffffffffu, l, 8);
                l += __shfl_xor_sync(0xffffffffu, l, 16);
                row_acquire();
#pragma unroll
                for (int a = 0; a < 3; a++) {
                    row[64 * a + 16 * t + g] = st.acc[a][0] + st.acc[a][1];
                    row[64 * a + 16 * t + g + 8] = st.acc[a][2] + st.acc[a][3];
                }
                if (lane == 0) { wbuf[8 * kWRow + w] = st.m; wbuf[8 * kWRow + 8 + w] = l; }
                row_publish();
            } else if (kind == OP_RFLOAD) {
#pragma unroll 1
                for (uint32_t tile = (op >> 3) & 7u; tile < (op >> 6); tile++) {
                    wait_tile(rpos);
#pragma unroll
                    for (int i = 0; i < 8; i++) {
                        if (tile == i) {
#pragma unroll
                            for (int k = 0; k < 6; k++) {
                                if (i & 1) ldsm4t(rf[i][k], frag_addr(rpos, k));
                                else ldsm4(rf[i][k], frag_addr(rpos, k));
                            }
                        }
                    }
                    ring_release();
                }
            } else if (kind == OP_QPROJ) {
                const uint32_t mask = (op >> 3) & 3u;
#pragma unroll 1
                for (uint32_t b = 0; b < 2; b++)
                    if ((mask >> b) & 1u) mbar_wait(sync0 + kBarXn + 8 * b, (op >> 5) & 1u);
                const uint32_t bb = mask == 3u ? (g & 1) : (mask >> 1);
                const uint32_t* xs = reinterpret_cast<const uint32_t*>(smem + kOffXn) + bb * 80 + 4 * w + t;
                float acc[3][4] = {};
#pragma unroll 1
                for (int p = 0; p < 3; p++) {
                    uint32_t xv = xs[p == 2 ? 48 : 32 * p];
                    if (p == 2 && w < 4) xv = 0u;
                    wait_tile(rpos);
#pragma unroll
                    for (int k = 0; k < 6; k++) {
                        uint32_t a[4];
                        ldsm4t(a, frag_addr(rpos, k));
                        mma16816(acc[k >> 1], a, (g >> 1) == 2 * (k & 1) ? xv : 0u, (g >> 1) == 2 * (k & 1) + 1 ? xv : 0u);
                    }
                    ring_release();
                }
#pragma unroll 1
                for (uint32_t b = 0; b < 2; b++) {
                    if (!((mask >> b) & 1u)) continue;
                    row_acquire();
#pragma unroll
                    for (int a = 0; a < 3; a++) {
                        row[64 * a + 16 * t + g] = b ? acc[a][1] : acc[a][0];
                        row[64 * a + 16 * t + g + 8] = b ? acc[a][3] : acc[a][2];
                    }
                    row_publish();
                }
            } else {
                const uint32_t mask = (op >> 3) & 3u;
                const uint32_t bb = mask == 3u ? (g & 1) : (mask >> 1);
                const uint32_t* ob = reinterpret_cast<const uint32_t*>(smem + kOffObf) + bb * 24 + t;
                const uint32_t roff = ((lane & 7) + 8 * (lane >> 4)) * 128 + ((((lane >> 3) & 1) ^ (lane & 7)) << 4);
                const bool ring = !(op >> 8);
                uint32_t sl[3];
#pragma unroll
                for (int p = 0; p < 3; p++) {
                    sl[p] = ring ? rpos : (op >> 8) + p;
                    if (ring && ++rpos == kRing) rpos = 0;
                }
                auto frag = [&](uint32_t (&a)[4], int p, int mt) {
                    ldsm4t(a, ((sbase + sl[p] * 8 * kSlotBytes + roff) ^ (((5 * w + mt) & 3) << 5)) + ((5 * w + mt) >> 2) * 2048);
                };
                uint32_t a0[5][4];
                wait_tile(sl[0]);
#pragma unroll
                for (int mt = 0; mt < 5; mt++) frag(a0[mt], 0, mt);
                if (ring) release(sl[0]);
                wait_tile(sl[1]);
                wait_tile(sl[2]);
                row_acquire();
                if (mask & 1u) mbar_wait(sync0 + kBarO, (op >> 5) & 1u);
                if (mask & 2u) mbar_wait(sync0 + kBarO + 8, (op >> 5) & 1u);
                TRACE_C(0);
                float c[3][4] = {};
#pragma unroll
                for (int p = 0; p < 3; p++) {
                    const uint32_t b0 = ob[8 * p], b1 = ob[8 * p + 4];
#pragma unroll
                    for (int mt = 0; mt < 5; mt++) {
                        if (p > 0) frag(a0[mt], p, mt);
                        const bool on = (g >> 1) == (mt & 3);
                        mma16816(c[mt == 4 ? 2 : (mt & 1)], a0[mt], on ? b0 : 0u, on ? b1 : 0u);
                    }
                    if (p > 0 && ring) release(sl[p]);
                }
                TRACE_C(1);
                row[16 * t + g] = c[0][0] + c[1][0]; row[80 + 16 * t + g] = c[0][1] + c[1][1];
                row[16 * t + g + 8] = c[0][2] + c[1][2]; row[80 + 16 * t + g + 8] = c[0][3] + c[1][3];
                if (t == 0) {
                    row[64 + g] = c[2][0]; row[144 + g] = c[2][1];
                    row[72 + g] = c[2][2]; row[152 + g] = c[2][3];
                }
                __syncwarp();
                if (lane < 27) {
                    const bool last = ((op >> 5) & 3u) == 3u;
                    float4* dst = last ? g_out[0][cta % kOutReplicas] + 27 * w + lane : g_acc[0][(op >> 5) & 3u] + (27 * w + lane) * kAccPad;
                    const float* y = row + 3 * lane;
                    if (mask & 1u) red_packet(dst, y[0], y[1], lane < 26 ? y[2] : 0.f);
                    if (mask & 2u) red_packet(dst + (last ? kOutReplicas : 3 * kAccPad) * kAccPackets, y[80], y[81], lane < 26 ? y[82] : 0.f);
                }
                TRACE_C(3);
                __syncwarp();
                if (lane < 2 && ((mask >> lane) & 1u)) mbar_arrive(sync0 + kBarSentY + 8 * lane);
            }
        }
    } else {
        asm volatile("setmaxnreg.dec.sync.aligned.u32 40;");
        if (w == 8) {
            if (elect()) {
    #pragma unroll
                for (int p = 0; p < kRing; p++) {
                        mbar_expect(sbase + kOffFull + 8 * p, 8 * kSlotBytes);
                    tma3d(sbase + p * 8 * kSlotBytes, &P.tm[4], 0, 160 * jq + (p == 2 ? 96 : 64 * p), 3 * h,
                          sbase + kOffFull + 8 * p, make_policy(false));
                    if (P.keepFirst) tma3d_prefetch(&P.tm[4], 0, 160 * jq + (p == 2 ? 96 : 64 * p), 3 * h, make_policy(true));
                }
            }
            __syncwarp();
            const int rowA = h * 4096 + 3072 + 256 * jq, rowB = h * 4096 + 1024 * jq;
            const int rowWq = 160 * jq, rowWo = 192 * h + 48 * jq;
            const uint32_t tau = P.tau, tauLow = P.tauLow, tauW = P.tauW;
            uint32_t credit = P.credit, na = 0;
            const uint32_t winLow = P.winLow, winHigh = P.winHigh;
            const uint64_t polKeep = make_policy(true), polStream = make_policy(false);
            uint32_t fifo = 0x012u, queued = 7u, stale = 0, par = 7u, nfl = kRing, next = now_ns() + P.startDelay;
            auto coord = [&](uint32_t e) {
                return (int)((e >> 10) & 0x7ffffu) + ((e & 4u) ? ((e & 2u) ? rowWo : rowWq) : ((e & 2u) ? rowB : rowA));
            };
            auto interval = [&](uint32_t e) { return (e & 4u) ? tauW : ((e & LD_LOW) ? tauLow : tau); };
            uint32_t recent = 0x012u;
            auto slot_free = [&](uint32_t s) { return mbar_test(sbase + kOffEmpty + 8 * s, ((par >> s) & 1u) ^ 1u); };
            auto landed = [&](uint32_t s) { return mbar_test(sbase + kOffFull + 8 * s, ((par >> s) & 1u) ^ 1u); };
            auto load = [&](uint32_t e, bool counted) {
                const uint32_t s = (e >> 4) & 15u;
                const int c1 = coord(e), c2 = ((e >> 1) & 3u) == 2u ? 3 * h : 0;
                if (elect()) {
                    mbar_expect(sbase + kOffFull + 8 * s, (e & 6u) == 6u ? 20480 : 8 * kSlotBytes);
                    const bool again = (e & (LD_KEEP | LD_HIT)) == (LD_KEEP | LD_HIT);
                    tma3d(sbase + s * 8 * kSlotBytes, &P.tm[e & 7u], 0, c1, c2, sbase + kOffFull + 8 * s, again ? polKeep : polStream);
                    if ((e & LD_KEEP) && !again) tma3d_prefetch(&P.tm[e & 7u], 0, c1, c2, polKeep);
                }
                if (counted) {
                    fifo = (fifo << 4) | s;
                    queued |= 1u << s;
                    nfl++;
                    recent = (recent << 4) | s;
                }
                par ^= 1u << s;
            };
            uint32_t m = 0, pfd = 0;
#pragma unroll 1
            for (uint32_t n = kRing;; n++) {
                const uint32_t e = P.loads[n];
                if (!(e & LD_VALID)) break;
                const uint32_t s = (e >> 4) & 15u;
                if (m < n) m = n;
                const uint32_t look = (e & LD_FAR) ? P.lookFar : P.look;
                for (uint32_t it = 0; !slot_free(s); it++) {
                    if (it > 16 * kSpinLimit) __trap();
                    if (PSLEEP) __nanosleep(PSLEEP);
                    const uint32_t f = P.loads[m];
                    if (m >= n + look || !(f & LD_VALID)) continue;
                    if (f & LD_HIT) { m++; continue; }
                    const uint32_t now = now_ns();
                    if ((int)(now - next) >= 0 && landed((recent >> (4 * P.lookBack)) & 15u)) {
                        if (elect()) tma3d_prefetch(&P.tm[f & 7u], 0, coord(f), ((f >> 1) & 3u) == 2u ? 3 * h : 0, polStream);
                        next = now + interval(f);
                        pfd |= 1u << (m & 31u);
                        m++;
                    }
                }
                stale |= queued & (1u << s);
                queued &= ~(1u << s);
                if (e & LD_ANCHOR) {
                    const uint32_t t0 = __shfl_sync(0xffffffffu, *reinterpret_cast<volatile uint32_t*>(smem + kOffAnchor), 0) + P.anchorDelay[na];
                    if (m <= n || (int)(t0 - next) > 0) next = t0;
                    credit = P.anchorCredit[na++];
                }
                const bool counted = !(e & LD_HIT) && !((pfd >> (n & 31u)) & 1u);
                pfd &= ~(1u << (n & 31u));
                if (counted) {
                    for (const uint32_t win = n < P.nStart ? P.winStart : ((e & LD_LOW) ? winLow : winHigh); nfl >= win; nfl--) {
                        const uint32_t o = (fifo >> (4 * nfl - 4)) & 15u;
                        if ((stale >> o) & 1u) {
                            stale ^= 1u << o;
                        } else {
                            mbar_wait_u(sbase + kOffFull + 8 * o, ((par >> o) & 1u) ^ 1u);
                            queued ^= 1u << o;
                        }
                    }
                    uint32_t now = now_ns();
                    while ((int)(now - next) < 0) { if (PSLEEP) __nanosleep(PSLEEP); now = now_ns(); }
                    if ((int)(now - credit - next) > 0) next = now - credit;
                    next += interval(e);
                }
                load(e, counted);
            }
        } else {
            if (w == 9) {
#pragma unroll 1
                for (int n = 0;; n++) {
                    const uint32_t job = P.merge[n];
                    if ((job & 3u) == MG_END) break;
                    const uint32_t b = (job >> 2) & 1u;
                    const uint32_t tag = 1 + ((job >> 3) & 3u);
                    mbar_wait(sync0 + kBarRows, n & 1);
                    if ((job & 3u) == MG_Q) {
#pragma unroll 1
                        for (int u = lane; u < 40; u += 32) {
                            float o[5] = {};
#pragma unroll
                            for (int i = 0; i < 8; i++)
#pragma unroll
                                for (int k = 0; k < 5; k++) o[k] += wbuf[i * kWRow + 5 * min(u, 38) + k];
                            st_packet5(&g_q[b][h][jq][u], o, tag);
                        }
                        __syncwarp();
                        if (lane == 0) mbar_arrive(sync0 + kBarSentQ + 8 * b);
                    } else {
                        float2* cp = reinterpret_cast<float2*>(smem + kOffCpart) + b * (kWRow / 2) + 3 * lane;
                        float2* cml = reinterpret_cast<float2*>(smem + kOffMl + 64) + b;
                        const float4* ml = reinterpret_cast<const float4*>(smem + kOffMl);
                        const bool merge = !(job & 32u);
                        const float2 pml = merge ? *cml : make_float2(-INFINITY, 0.f);
                        const float4 m0 = ml[0], m1 = ml[1];
                        float sc[8] = {m0.x, m0.y, m0.z, m0.w, m1.x, m1.y, m1.z, m1.w};
                        const float M = fmaxf(fmaxf(fmaxf(fmaxf(sc[0], sc[1]), fmaxf(sc[2], sc[3])),
                                                    fmaxf(fmaxf(sc[4], sc[5]), fmaxf(sc[6], sc[7]))), pml.x);
#pragma unroll
                        for (int i = 0; i < 8; i++) sc[i] = ex2(sc[i] - M);
                        const float ps = ex2(pml.x - M);
                        float2 o[3];
#pragma unroll
                        for (int k = 0; k < 3; k++) {
                            o[k] = merge ? cp[k] : make_float2(0.f, 0.f);
                            o[k].x *= ps; o[k].y *= ps;
                        }
#pragma unroll
                        for (int i = 0; i < 8; i++)
#pragma unroll
                            for (int k = 0; k < 3; k++) {
                                const float2 v = reinterpret_cast<const float2*>(wbuf)[i * (kWRow / 2) + 3 * lane + k];
                                o[k].x = fmaf(v.x, sc[i], o[k].x);
                                o[k].y = fmaf(v.y, sc[i], o[k].y);
                            }
                        const float4 l0 = ml[2], l1 = ml[3];
                        const float L = fmaf(pml.y, ps, ((l0.x * sc[0] + l0.y * sc[1]) + (l0.z * sc[2] + l0.w * sc[3])) +
                                                        ((l1.x * sc[4] + l1.y * sc[5]) + (l1.z * sc[6] + l1.w * sc[7])));
                        if (job & 64u) {
                            uint4* dst = &g_p[b][h][lane >> 3][jq][2 * (lane & 7)];
                            st_packet(dst, o[0].x, o[0].y, o[1].x, tag);
                            st_packet(dst + 1, o[1].y, o[2].x, o[2].y, tag);
                            if (lane < 8) st_packet(&g_p[b][h][lane >> 1][jq][16 + (lane & 1)], M, L, 0.f, tag);
                            if (lane == 0) mbar_arrive(sync0 + kBarSentP + 8 * b);
                        } else {
#pragma unroll
                            for (int k = 0; k < 3; k++) cp[k] = o[k];
                            __syncwarp();
                            if (lane == 0) *cml = make_float2(M, L);
                        }
                    }
                    __syncwarp();
                    if (lane == 0) mbar_arrive(sync0 + kBarFree);
                }
            } else {
                const uint32_t b = w - 10;
                __nv_bfloat16* const xn = reinterpret_cast<__nv_bfloat16*>(smem + kOffXn) + b * 160;
                __nv_bfloat16* const qd = reinterpret_cast<__nv_bfloat16*>(smem + kOffQf) + b * 192;
                __nv_bfloat16* const ob = reinterpret_cast<__nv_bfloat16*>(smem + kOffObf) + b * 48;
                uint2* const own = reinterpret_cast<uint2*>(smem + kOffOwn) + 2 * b;
#pragma unroll 1
                for (uint32_t layer = 0; layer < 4; layer++) {
                    const uint32_t tag = layer + 1;
                    {
                        int lane = fresh_lane();
                        uint32_t x01[7], x2[7];
                        if (layer == 0) {
                            const uint4* stage = reinterpret_cast<const uint4*>(wbuf) + 80 * b;
                            asm volatile("cp.async.wait_all;" ::: "memory");
                            __syncwarp();
#pragma unroll
                            for (int i = 0; i < 7; i++) {
                                const int p = lane + 32 * i, u = p % 27;
                                const unsigned short* xp = reinterpret_cast<const unsigned short*>(stage) + (p / 27) * 80 + 3 * u;
                                x01[i] = p < kAccPackets ? xp[0] | ((uint32_t)xp[1] << 16) : 0u;
                                x2[i] = (p < kAccPackets && u < 26) ? xp[2] : 0u;
                            }
                        } else {
                            mbar_wait(sync0 + kBarSentY + 8 * b, (layer - 1) & 1);
                            TRACE_G(4 * layer - 1);
                            pause_ns(P.xDelay);
                            uint4 v[7];
                            const uint4* src = reinterpret_cast<const uint4*>(&g_acc[b][layer - 1][lane * kAccPad]);
                            const uint32_t done = __float_as_uint(kAccDone);
                            POLL_UNTIL(SLEEPNS, v[0] = ld_packet(src + (27 * (cta & 7) + min(lane, 26) - lane) * kAccPad), v[0].w == done);
                            POLL_UNTIL(SLEEPNS,
                                v[0] = ld_packet(src); v[1] = ld_packet(src + 32 * kAccPad); v[2] = ld_packet(src + 64 * kAccPad);
                                v[3] = ld_packet(src + 96 * kAccPad); v[4] = ld_packet(src + 128 * kAccPad);
                                v[5] = ld_packet(src + 160 * kAccPad); v[6] = ld_packet(src + (lane < 24 ? 192 * kAccPad : 0)),
                                v[0].w == done && v[1].w == done && v[2].w == done && v[3].w == done && v[4].w == done &&
                                    v[5].w == done && v[6].w == done);
#pragma unroll
                            for (int i = 0; i < 7; i++) {
                                x01[i] = pack_bf16(__uint_as_float(v[i].x), __uint_as_float(v[i].y));
                                x2[i] = pack_bf16(__uint_as_float(v[i].z), 0.f);
                            }
                            if (lane >= 24) x01[6] = x2[6] = 0u;
                        }
                        TRACE_G(16 + 4 * layer);
#pragma unroll
                        for (int i = 0; i < 7; i++) {
                            const int p = lane + 32 * i;
                            if ((p & 127) == cta && p < kAccPackets) {
                                own[i >> 2] = make_uint2(x01[i], x2[i]);
                            }
                        }
                        float sum = 0.f;
#pragma unroll
                        for (int i = 0; i < 7; i++) sum += (bf_lo(x01[i]) + bf_hi(x01[i])) + bf_lo(x2[i]);
                        const float mean = warp_sum(sum) * (1.f / 640.f);
                        float sq = 0.f;
#pragma unroll
                        for (int i = 0; i < 7; i++) {
                            const bool none = i == 6 && lane >= 24;
                            const float d0 = none ? 0.f : bf_lo(x01[i]) - mean, d1 = none ? 0.f : bf_hi(x01[i]) - mean;
                            const bool last = lane == 26 - 5 * i || lane == 53 - 5 * i;
                            const float d2 = (none || last) ? 0.f : bf_lo(x2[i]) - mean;
                            sq += fmaf(d0, d0, fmaf(d1, d1, d2 * d2));
                        }
                        const float var = warp_sum(sq) * (1.f / 640.f);
                        const float meanb = bf16r(mean);
                        const float rden = __fdividef(1.f, bf16r(fast_sqrt(bf16r(bf16r(var) + 1e-5f))));
#pragma unroll
                        for (int i = 0; i < 7; i++) {
                            const uint32_t q = lane + 32 * i - 54 * jq;
                            if (q < 54u) {
                                const int c = 3 * q - (q >= 27u);
                                xn[c] = __float2bfloat16_rn(bf16r(bf_lo(x01[i]) - meanb) * rden);
                                xn[c + 1] = __float2bfloat16_rn(bf16r(bf_hi(x01[i]) - meanb) * rden);
                                if (q != 26u && q != 53u) xn[c + 2] = __float2bfloat16_rn(bf16r(bf_lo(x2[i]) - meanb) * rden);
                            }
                        }
                        if (lane == 0) *reinterpret_cast<volatile uint32_t*>(smem + kOffAnchor) = now_ns();
                        __syncwarp();
                        if (lane == 0) mbar_arrive(sync0 + kBarXn + 8 * b);
                        TRACE_G(4 * layer);
                        if (layer >= 2 && lane < 4 && cta + 128 * (lane >> 1) < kAccPackets)
                            g_acc[b][layer - 2][(cta + 128 * (lane >> 1)) * kAccPad + (lane & 1)] = make_float4(0.f, 0.f, 0.f, 0.f);
                        __syncwarp();
                    }
                    {
                        const int lane = fresh_lane();
                        mbar_wait(sync0 + kBarSentQ + 8 * b, layer & 1);
                        pause_ns((layer == 0 || (layer == 1 && b == 1)) ? P.qDelay : P.qDelay2);
                        uint4 v[5];
                        const uint4* src = &g_q[b][h][0][lane];
                        const uint4* ext = &g_q[b][h][lane & 3][lane < 28 ? 32 + (lane >> 2) : 38];
                        POLL_UNTIL(SLEEPQ,
                            v[0] = ld_packet(src); v[1] = ld_packet(src + 40); v[2] = ld_packet(src + 80);
                            v[3] = ld_packet(src + 120); v[4] = ld_packet(ext),
                            (v[0].w >> 24) == tag && (v[1].w >> 24) == tag && (v[2].w >> 24) == tag &&
                                (v[3].w >> 24) == tag && (v[4].w >> 24) == tag);
                        __syncwarp();
                        TRACE_G(16 + 4 * layer + 1);
                        auto store_q = [&](int d, float q) {
                            qd[(d & ~31) + ((d >> 3) & 1) * 16 + ((d >> 1) & 3) * 4 + ((d >> 4) & 1) * 2 + (d & 1)] =
                                __float2bfloat16_rn(q);
                        };
                        float a[5] = {};
#pragma unroll
                        for (int i = 0; i < 4; i++) add_packet5(a, v[i]);
#pragma unroll
                        for (int k = 0; k < 5; k++) store_q(5 * lane + k, a[k]);
                        float e[5] = {};
                        add_packet5(e, v[4]);
#pragma unroll
                        for (int k = 0; k < 5; k++) {
                            e[k] += __shfl_xor_sync(0xffffffffu, e[k], 1);
                            e[k] += __shfl_xor_sync(0xffffffffu, e[k], 2);
                            const int d = 160 + 5 * (lane >> 2) + k;
                            if ((lane & 3) == 0 && d < 192) store_q(d, e[k]);
                        }
                        __syncwarp();
                        if (lane == 0) mbar_arrive(sync0 + kBarQ + 8 * b);
                        TRACE_G(4 * layer + 1);
                    }
                    if (P.exp) break;
                    {
                        const int lane = fresh_lane();
                        mbar_wait(sync0 + kBarSentP + 8 * b, layer & 1);
                        pause_ns((b == 0 && (layer == 0 || layer == 3)) ? P.qDelay : (layer == 3 ? 0 : P.pDelay));
                        uint4 v0, v1, ml;
                        const uint4* src = &g_p[b][h][jq][2 * (lane >> 4)][lane & 15];
                        const uint4* mls = &g_p[b][h][jq][lane & 3][16];
                        POLL_UNTIL(SLEEPQ, v0 = ld_packet(src); v1 = ld_packet(src + 18); ml = ld_packet(mls),
                                   v0.w == tag && v1.w == tag && ml.w == tag);
                        __syncwarp();
                        TRACE_G(16 + 4 * layer + 2);
                        const float mi = __uint_as_float(ml.x);
                        float M = fmaxf(mi, __shfl_xor_sync(0xffffffffu, mi, 1));
                        M = fmaxf(M, __shfl_xor_sync(0xffffffffu, M, 2));
                        const float sc = ex2(mi - M);
                        float L = __uint_as_float(ml.y) * sc;
                        L += __shfl_xor_sync(0xffffffffu, L, 1);
                        L += __shfl_xor_sync(0xffffffffu, L, 2);
                        const float s0 = __shfl_sync(0xffffffffu, sc, 2 * (lane >> 4));
                        const float s1 = __shfl_sync(0xffffffffu, sc, 2 * (lane >> 4) + 1);
                        float o0 = fmaf(__uint_as_float(v0.x), s0, __uint_as_float(v1.x) * s1);
                        float o1 = fmaf(__uint_as_float(v0.y), s0, __uint_as_float(v1.y) * s1);
                        float o2 = fmaf(__uint_as_float(v0.z), s0, __uint_as_float(v1.z) * s1);
                        o0 += __shfl_xor_sync(0xffffffffu, o0, 16);
                        o1 += __shfl_xor_sync(0xffffffffu, o1, 16);
                        o2 += __shfl_xor_sync(0xffffffffu, o2, 16);
                        if (lane < 16) {
                            ob[3 * lane] = __float2bfloat16_rn(__fdividef(o0, L));
                            ob[3 * lane + 1] = __float2bfloat16_rn(__fdividef(o1, L));
                            ob[3 * lane + 2] = __float2bfloat16_rn(__fdividef(o2, L));
                        }
                        __syncwarp();
                        if (lane == 0) mbar_arrive(sync0 + kBarO + 8 * b);
                        const int p = cta + 128 * lane;
                        if (p < kAccPackets) {
                            const uint2 v = own[lane];
                            red_packet(layer == 3 ? g_out[b][0] + p : g_acc[b][layer] + p * kAccPad, bf_lo(v.x), bf_hi(v.x), bf_lo(v.y));
                        }
                        TRACE_G(4 * layer + 2);
                    }
                }
                if (!P.exp) {
                    mbar_wait(sync0 + kBarSentY + 8 * b, 1);
                    const int p = cta + 128 * ((lane >> 3) & 1), r = lane & 7;
                    float4* src = &g_out[b][r][p < kAccPackets ? p : cta];
                    const float want = kCtas / kOutReplicas + (r == 0);
                    uint4 v;
                    for (uint32_t it = 0;; it++) {
                        v = ld_packet(reinterpret_cast<const uint4*>(src));
                        if (__all_sync(0xffffffffu, v.w == __float_as_uint(want))) break;
                        if (it > kSpinLimit) __trap();
                    }
                    float o0 = __uint_as_float(v.x), o1 = __uint_as_float(v.y), o2 = __uint_as_float(v.z);
#pragma unroll
                    for (int o = 1; o < 8; o <<= 1) {
                        o0 += __shfl_xor_sync(0xffffffffu, o0, o);
                        o1 += __shfl_xor_sync(0xffffffffu, o1, o);
                        o2 += __shfl_xor_sync(0xffffffffu, o2, o);
                    }
                    if (lane < 16 && p < kAccPackets) {
                        if (r < 3 - (p % 27 == 26))
                            P.out[b * 640 + (p / 27) * 80 + 3 * (p % 27) + r] = __float2bfloat16_rn(r == 0 ? o0 : r == 1 ? o1 : o2);
                        *src = make_float4(0.f, 0.f, 0.f, 0.f);
                        if (r == 0) g_acc[b][2][p * kAccPad] = make_float4(0.f, 0.f, 0.f, 0.f);
                    }
                    TRACE_G(15);
                }
            }
        }
    }
}

struct Sched {
    Params& P;
    int np = 0, nm = 0, nl = 0, rslot = 0, mark = 0;
    uint32_t pending = 0;
    enum { RF = 1 << 7, FIRST = 1 << 11, PUB = 1 << 12 };
    void low_begin(int back) { mark = nl - back; }
    void low_end(int back) { for (int i = mark; i < nl - back; i++) P.loads[i] |= LD_LOW; }
    void slot(uint32_t e, int s) { P.loads[nl++] = e | (s << 4); }
    void ring(uint32_t e) {
        slot(e | pending, rslot);
        pending = 0;
        rslot = (rslot + 1) % kRing;
    }
    static uint32_t tile(int isB, int b, int idx, int v) {
        return LD_VALID | (2 * isB + v) | (uint32_t)(b * 32 * 4096 + 64 * idx) << 10;
    }
    static uint32_t wq(int layer, int p) { return LD_VALID | (4 + (layer & 1)) | (p == 2 ? 96 : 64 * p) << 10; }
    static uint32_t wo(int layer, int p) { return LD_VALID | (6 + (layer & 1)) | (16 * p) << 10; }
    void kv(int isB, int b, int idx, uint32_t fk = 0, uint32_t fv = 0) {
        ring(tile(isB, b, idx, 0) | fk);
        ring(tile(isB, b, idx, 1) | fv);
    }
    void ret(int b, int idx, int pair) {
        slot(tile(1, b, idx, 0), kRing + 2 * pair);
        slot(tile(1, b, idx, 1), kRing + 2 * pair + 1);
    }
    const char* wuse = "";
    uint32_t wflags() {
        const char c = *wuse ? *wuse++ : '-';
        return ((c == 'k' || c == 'b') ? LD_KEEP : 0u) | ((c == 'h' || c == 'b') ? LD_HIT : 0u);
    }
    void qproj(int mask, int layer, uint32_t f = 0, bool anchor = true) {
        f |= wflags();
        for (int p = 0; p < 3; p++) ring(wq(layer, p) | f);
        if (anchor) pending = LD_ANCHOR;
        P.prog[np++] = OP_QPROJ | (mask << 3) | (layer << 5);
        for (int b = 0; b < 2; b++)
            if ((mask >> b) & 1) P.merge[nm++] = MG_Q | (b << 2) | (layer << 3);
    }
    void oproj(int mask, int layer, uint32_t f = 0, int firstSlot = 0) {
        f |= wflags();
        if (!firstSlot) for (int p = 0; p < 3; p++) ring(wo(layer, p) | f);
        P.prog[np++] = OP_OPROJ | (mask << 3) | (layer << 5) | (firstSlot << 8);
    }
    void rfload(int from, int to, int isB, int b, int idx0) {
        if (from >= to) return;
        for (int i = from; i < to; i++) ring(tile(isB, b, idx0 + i / 2, i & 1));
        P.prog[np++] = OP_RFLOAD | (from << 3) | (to << 6);
    }
    void seg(int b, int layer, uint32_t flags, const char* order, int nrel = 0) {
        uint64_t list = 0;
        int nr = 0;
        for (int n = 0; order[n]; n++) {
            const char c = order[n];
            uint64_t it = 12;
            if (c == 'r') { it = 8 | (nr < nrel ? 4 : 0) | (nr % 3 + 1); nr++; }
            else if (c >= 'a' && c <= 'c') it = 12 | (c - 'a' + 1);
            else if (c >= 'A' && c <= 'C') it = 8 | (c - 'A' + 1);
            list |= it << (4 * n);
        }
        P.prog[np++] = OP_SEG | (b << 3) | ((layer & 1) << 4) | (flags & RF);
        P.prog[np++] = (uint32_t)list;
        P.prog[np++] = (uint32_t)(list >> 32);
        P.merge[nm++] = MG_ATTN | (b << 2) | (layer << 3) | ((flags & FIRST) ? 32 : 0) | ((flags & PUB) ? 64 : 0);
    }
    void seg(int b, int layer, uint32_t flags, int nring) { seg(b, layer, flags, &"dddddddddddddddd"[16 - nring]); }
};

const char* tune_str(const char* name, const char* dflt) {
    (void)name;
    return dflt;
}

int tune(const char* name, int dflt) {
    (void)name;
    return dflt;
}

void build_schedule(Params& P) {
    for (int i = 0; i < kMaxProg; i++) P.prog[i] = P.merge[i] = 0;
    for (int i = 0; i < kMaxLoads; i++) P.loads[i] = LD_NONE;
    P.winLow = tune("WINLOW", 3);
    P.winHigh = tune("WINHIGH", 3);
    P.tau = tune("TAU", 965);
    P.tauLow = tune("TAULOW", 1000);
    P.tauW = tune("TAUW", P.tauLow * 5 / 6);
    P.credit = tune("CREDIT", 700);
    for (int i = 0; i < 6; i++) {
        const char dn[4] = {'A', 'D', (char)('0' + i), 0}, cn[4] = {'A', 'C', (char)('0' + i), 0};
        P.anchorDelay[i] = tune(dn, tune("ADELAY", 200));
        P.anchorCredit[i] = tune(cn, i == 1 ? 1500 : i == 4 ? 300 : P.credit);
    }
    P.startDelay = tune("STARTDELAY", 1000);
    P.look = tune("LOOK", 3);
    P.lookBack = tune("LOOKBACK", 0);
    P.nStart = tune("NSTART", 10);
    P.winStart = tune("WINSTART", 4);
    P.lookFar = tune("LOOKFAR", 4);

    Sched S{P};
    using F = Sched;
    S.wuse = tune_str("WK", "k-k-h-h-----");
    const int keep[2] = {tune("KEEP0", 9), tune("KEEP1", 10)};
    auto flag = [&](int b, int idx, int v, uint32_t f) { return (2 * (15 - idx) + (1 - v)) < keep[b] ? f : 0u; };
    const int hit[2] = {16 - (keep[0] + 1) / 2, 16 - (keep[1] + 1) / 2};
    int next0 = 3, next1 = 7, nextA = 0;
    auto first0 = [&](const char* order, uint32_t flags) {
        for (const char* c = order; *c; c++)
            if (*c != 'r') {
                S.kv(1, 0, next0, flag(0, next0, 0, LD_KEEP), flag(0, next0, 1, LD_KEEP));
                next0++;
            }
        S.seg(0, 1, flags, order);
    };
    auto fillA = [&](const char* order, uint32_t flags) {
        int nr = 0;
        for (const char* c = order; *c; c++) if (*c == 'r') nr++; else S.kv(0, 1, nextA++);
        S.seg(1, 0, flags, order, nr);
    };
    auto fill0 = [&](int n, uint32_t flags = 0) {
        int c = 0;
        for (; c < n && next0 < hit[0]; c++) S.kv(1, 0, next0++);
        if (c > 0 || flags) S.seg(0, 3, flags, c);
    };
    auto fill1 = [&](int n) {
        int c = 0;
        const uint32_t flags = next1 == 7 ? F::FIRST : 0;
        for (; c < n && next1 < hit[1]; c++) S.kv(1, 1, next1++);
        if (c > 0) S.seg(1, 1, flags, c);
    };
    int nextH[2] = {hit[0], hit[1]}, nextK = hit[1], nextD1 = 10;
    bool started[2] = {};
    auto phase = [&](const char* spec, const int (&layer)[2], int refill0, const char* pos, int pubMask) {
        int tiles = 0, nq = 0, done = 0, due[8] = {};
        uint32_t ent[8] = {};
        auto flush = [&](int upto) { while (done < nq && due[done] <= upto) P.loads[S.nl++] = ent[done++]; };
        for (const char* c = spec; *c; c++) {
            if (!nq && (*c == 'h' || *c == 'd' || *c == 'k')) tiles += 2;
            if (*c >= 'a' && *c <= 'c')
                for (int v = 0; v < 2; v++, nq++) {
                    due[nq] = tiles + (pos[nq] <= '9' ? pos[nq] - '0' : pos[nq] - 'a' + 10);
                    ent[nq] = F::tile(1, 1, refill0 + nq / 2, v) | LD_FAR | ((kRing + 2 * (*c - 'a') + v) << 4);
                }
        }
        tiles = 0;
        for (const char* c = spec; *c;) {
            const int b = *c++ - '0';
            char order[20];
            int n = 0;
            uint32_t flags = started[b] ? 0 : F::FIRST;
            started[b] = true;
            for (; *c && *c != '.'; c++) {
                if (*c == 'R') { flags |= F::RF; continue; }
                order[n++] = *c;
                if (*c != 'h' && *c != 'd' && *c != 'k') continue;
                const int idx = *c == 'h' ? nextH[b]++ : *c == 'k' ? nextK++ : b ? nextD1++ : next0++;
                for (int v = 0; v < 2; v++, tiles++) {
                    flush(tiles);
                    S.ring(F::tile(1, b, idx, v) | LD_FAR | flag(b, idx, v, *c == 'h' ? LD_HIT : *c == 'k' ? LD_KEEP : 0));
                }
            }
            order[n] = 0;
            bool last = true;
            for (const char* r = c; *r; r++) if (*r == '.' && r[1] - '0' == b) last = false;
            S.seg(b, layer[b], flags | ((last && ((pubMask >> b) & 1)) ? F::PUB : 0), order);
            if (*c) c++;
        }
        flush(1 << 20);
    };

    P.keepFirst = 0;
    P.xDelay = tune("XDELAY", 1400);
    P.qDelay2 = tune("QDELAY2", 0);
    P.pDelay = tune("PDELAY", 1000);
    P.qDelay = tune("QDELAY", 3500);

    P.exp = tune("EXP", 0);
    if (P.exp) {
        S.qproj(3, 0);
        for (int r = 0; r < 2; r++)
            for (int b = 0; b < 2; b++) {
                for (int i = 0; i < 15; i++) S.kv(1, b, i);
                S.seg(b, 0, F::FIRST, 15);
            }
        return;
    }
    const int lb = tune("LOWBACK", 0);
    const int early = tune("EARLY", 1);
    S.qproj(3, 0, 0, false);
    P.keepFirst = P.loads[0] & LD_KEEP;
    for (int i = 0; i < early; i++) {
        S.slot(F::tile(0, 1, i, 0), kRing + 2 * i);
        S.slot(F::tile(0, 1, i, 1), kRing + 2 * i + 1);
    }
    S.rfload(0, 8, 0, 0, 0);
    S.seg(0, 0, F::RF | F::FIRST | F::PUB, 0);
    S.low_begin(lb);
    if (tune("JOINT", 1)) {
        nextA = early;
        fillA(tune_str("LA", "rddd"), F::FIRST | F::PUB);
        const int r0 = tune("RET0", 0), r1 = r0 + tune("RET1", 4);
        auto ret_tiles = [&](int from, int to) { for (int i = from; i < to; i++) S.slot(F::tile(1, 0, i / 2, i & 1), kRing + i); };
        ret_tiles(6 - r0, 6);
        S.oproj(3, 0);
        ret_tiles(0, r1 - r0);
        S.qproj(3, 1);
        ret_tiles(r1 - r0, 6 - r0);
        S.low_end(0);
        first0(tune_str("L2", "dddrdddrdddrdddd"), F::FIRST | F::PUB);
    } else {
        nextA = early;
        fillA(tune_str("LA1", "d"), F::FIRST);
        S.oproj(1, 0, LD_KEEP);
        fillA(tune_str("LA2", "ddd"), F::PUB);
        S.qproj(1, 1, LD_KEEP);
        S.pending = 0;
        P.loads[S.nl] = 0;
        S.ret(0, 0, 0);
        P.loads[S.nl - 2] |= tune("RETANCHOR", 0) ? LD_ANCHOR : 0;
        S.oproj(2, 0, LD_HIT);
        S.ret(0, 1, 1);
        S.ret(0, 2, 2);
        first0(tune_str("L2A", "ddd"), F::FIRST);
        S.qproj(2, 1, LD_HIT);
        S.low_end(0);
        first0(tune_str("L2B", "drddrddrddddd"), F::PUB);
    }
    next0 = 3;
    S.low_begin(lb);
    fill1(tune("F21", 0));
    S.oproj(1, 1);
    fill1(tune("F22", 2));
    S.qproj(1, 2);
    fill1(tune("F23", 1));
    S.seg(0, 2, F::RF | F::FIRST | F::PUB, 0);
    const int r1 = tune("R31", 2), r2 = r1 + tune("R32", 4);
    S.rfload(0, r1, 1, 1, 3);
    fill1(tune("F31", 0));
    S.oproj(1, 2);
    S.rfload(r1, r2, 1, 1, 3);
    fill1(tune("F32", 1));
    S.qproj(1, 3);
    S.rfload(r2, 8, 1, 1, 3);
    fill1(16);
    S.low_end(0);
    started[1] = next1 > 7;
    phase(tune_str("P4", "0ahbchhhh.1RkkkAkBCk"), {3, 1}, 0, tune_str("POS4", "334577"), 2);
    S.low_begin(lb);
    fill0(tune("F41", 0));
    S.oproj(2, 1);
    fill0(tune("F42", 2));
    S.qproj(2, 2);
    fill0(tune("F43", 1));
    for (int i = 0; i < 4; i++) S.kv(0, 1, i);
    S.seg(1, 2, F::FIRST | F::PUB, 4);
    fill0(tune("F51", 1));
    S.oproj(2, 2);
    fill0(tune("F52", 2));
    S.qproj(2, 3);
    fill0(tune("F53", 0));
    S.low_end(0);
    started[1] = false;
    phase(tune_str("P6", "0dd.1RabdchhhAhBhC"), {3, 3}, 7, tune_str("POS6", "33579b"), 3);
    S.oproj(3, 3);
}

typedef CUresult (*EncodeFn)(CUtensorMap*, CUtensorMapDataType, cuuint32_t, void*, const cuuint64_t*,
                             const cuuint64_t*, const cuuint32_t*, const cuuint32_t*, CUtensorMapInterleave,
                             CUtensorMapSwizzle, CUtensorMapL2promotion, CUtensorMapFloatOOBfill);

}

extern "C" void kernel_launch(void* const* d_in, const int* in_sizes, int n_in, void* d_out, int out_size) {
    (void)in_sizes; (void)n_in; (void)out_size;
    Params P;
    void* fn = nullptr;
    cudaDriverEntryPointQueryResult qr;
    cudaGetDriverEntryPoint("cuTensorMapEncodeTiled", &fn, cudaEnableDefault, &qr);
    EncodeFn encode = reinterpret_cast<EncodeFn>(fn);
    const CUtensorMapL2promotion promo = (CUtensorMapL2promotion)tune("PROMO", CU_TENSOR_MAP_L2_PROMOTION_NONE);
    void* kv[4] = {d_in[1], d_in[2], d_in[6], d_in[7]};
    for (int i = 0; i < 4; i++) {
        const cuuint64_t dims[3] = {64, 2ull * 32 * 4096, 3};
        const cuuint64_t strides[2] = {384, 128};
        const cuuint32_t box[3] = {64, 64, 3};
        const cuuint32_t es[3] = {1, 1, 1};
        encode(&P.tm[i], CU_TENSOR_MAP_DATA_TYPE_BFLOAT16, 3, kv[i], dims, strides, box, es,
               CU_TENSOR_MAP_INTERLEAVE_NONE, CU_TENSOR_MAP_SWIZZLE_128B, promo, CU_TENSOR_MAP_FLOAT_OOB_FILL_NONE);
    }
    void* wq[2] = {d_in[3], d_in[8]};
    for (int i = 0; i < 2; i++) {
        const cuuint64_t dims[3] = {64, 640, 96};
        const cuuint64_t strides[2] = {12288, 128};
        const cuuint32_t box[3] = {64, 64, 3};
        const cuuint32_t es[3] = {1, 1, 1};
        encode(&P.tm[4 + i], CU_TENSOR_MAP_DATA_TYPE_BFLOAT16, 3, wq[i], dims, strides, box, es,
               CU_TENSOR_MAP_INTERLEAVE_NONE, CU_TENSOR_MAP_SWIZZLE_128B, promo, CU_TENSOR_MAP_FLOAT_OOB_FILL_NONE);
    }
    void* wo[2] = {d_in[4], d_in[9]};
    for (int i = 0; i < 2; i++) {
        const cuuint64_t dims[3] = {64, 6144, 10};
        const cuuint64_t strides[2] = {1280, 128};
        const cuuint32_t box[3] = {64, 16, 10};
        const cuuint32_t es[3] = {1, 1, 1};
        encode(&P.tm[6 + i], CU_TENSOR_MAP_DATA_TYPE_BFLOAT16, 3, wo[i], dims, strides, box, es,
               CU_TENSOR_MAP_INTERLEAVE_NONE, CU_TENSOR_MAP_SWIZZLE_128B, promo, CU_TENSOR_MAP_FLOAT_OOB_FILL_NONE);
    }
    P.x = static_cast<const __nv_bfloat16*>(d_in[0]);
    P.out = static_cast<__nv_bfloat16*>(d_out);
    build_schedule(P);
    cudaFuncSetAttribute(fused_decode_kernel, cudaFuncAttributeMaxDynamicSharedMemorySize, kSmemBytes);
    fused_decode_kernel<<<kCtas, kThreads, kSmemBytes>>>(P);
}
```

```cpp
#include <cuda_runtime.h>
#include <cuda_bf16.h>
#include <cuda.h>
#include <stdint.h>

namespace {

constexpr int kCtas = 128;
constexpr int kThreads = 384;
constexpr int kSlotBytes = 3072;
constexpr int kRing = 3;
constexpr int kSlots = 9;
constexpr int kWRow = 192;

constexpr int kOffWbuf = kSlots * 8 * kSlotBytes;
constexpr int kOffMl = kOffWbuf + 8 * kWRow * 4;
constexpr int kOffCpart = kOffMl + 20 * 4;
constexpr int kOffQf = kOffCpart + 2 * kWRow * 4;
constexpr int kOffXn = kOffQf + 2 * 96 * 4;
constexpr int kOffObf = kOffXn + 2 * 160 * 2;
constexpr int kOffFull = kOffObf + 2 * 48 * 2;
constexpr int kOffEmpty = kOffFull + kSlots * 8;
constexpr int kOffSync = kOffEmpty + kSlots * 8;
constexpr int kOffAnchor = kOffSync + 14 * 8;
constexpr int kOffOwn = kOffAnchor + 8;
constexpr int kSmemBytes = kOffOwn + 32;
static_assert(kSmemBytes <= 232448, "shared memory budget");
constexpr int kBarRows = 0, kBarFree = 8, kBarQ = 16, kBarXn = 32, kBarO = 48;
constexpr int kBarSentQ = 64, kBarSentP = 80, kBarSentY = 96;

constexpr int kMaxProg = 72;
constexpr int kMaxMerge = 32;
constexpr int kMaxLoads = 176;
constexpr int kAnchors = 5;

constexpr uint32_t kTau = 970;
constexpr uint32_t kTauHandoff = 1000;
constexpr uint32_t kTauWo = 833;
constexpr uint32_t kCredit = 700;
constexpr uint32_t kWindow = 3;
constexpr uint32_t kStartWindow = 4, kStartLoads = 10, kStartDelay = 1000;
constexpr uint32_t kLook = 3, kLookFar = 4;
constexpr uint32_t kDelayX = 2200, kDelayP = 1000, kDelayIdle = 2500, kPauseX = 200;

enum : uint32_t { OP_END = 0, OP_QPROJ = 1, OP_RFLOAD = 2, OP_SEG = 3, OP_OPROJ = 4 };
enum : uint32_t { MG_END = 0, MG_ATTN = 1, MG_Q = 2 };
enum : uint32_t {
    LD_KEEP = 1u << 3,
    LD_HANDOFF = 1u << 8,
    LD_VALID = 1u << 9,
    LD_HALF = 1u << 28,
    LD_ANCHOR = 1u << 29,
    LD_FAR = 1u << 30,
    LD_HIT = 1u << 31
};

struct alignas(64) Params {
    CUtensorMap tm[10];
    const __nv_bfloat16* x;
    __nv_bfloat16* out;
    uint32_t anchorDelay[kAnchors], anchorCredit[kAnchors];
    uint32_t prog[kMaxProg];
    uint32_t merge[kMaxMerge];
    uint32_t loads[kMaxLoads];
};

__device__ uint4 g_q[2][32][4][40];
__device__ uint4 g_p[2][32][4][4][18];
constexpr int kAccPackets = 216;
constexpr float kAccDone = 129.f;
constexpr int kAccPad = 2;
__device__ float4 g_acc[2][3][kAccPackets * kAccPad];
constexpr int kOutReplicas = 8;
__device__ float4 g_out[2][kOutReplicas][kAccPackets * kAccPad];

constexpr uint32_t kSpinLimit = 1u << 22;

__device__ __forceinline__ void mbar_init(uint32_t bar, uint32_t count) {
    asm volatile("mbarrier.init.shared::cta.b64 [%0], %1;" ::"r"(bar), "r"(count) : "memory");
}
__device__ __forceinline__ void mbar_arrive(uint32_t bar) {
    asm volatile("mbarrier.arrive.shared::cta.b64 _, [%0];" ::"r"(bar) : "memory");
}
__device__ __forceinline__ bool mbar_test(uint32_t bar, uint32_t parity) {
    uint32_t ok;
    asm volatile(
        "{\n\t.reg .pred p;\n\t"
        "mbarrier.test_wait.parity.shared::cta.b64 p, [%1], %2;\n\t"
        "selp.u32 %0, 1, 0, p;\n\t}"
        : "=r"(ok) : "r"(bar), "r"(parity) : "memory");
    return __all_sync(0xffffffffu, ok);
}
__device__ __forceinline__ void mbar_expect(uint32_t bar, uint32_t bytes) {
    asm volatile("mbarrier.arrive.expect_tx.shared::cta.b64 _, [%0], %1;" ::"r"(bar), "r"(bytes) : "memory");
}
__device__ __forceinline__ void mbar_wait(uint32_t bar, uint32_t parity) {
    uint32_t ok, it = 0;
    do {
        asm volatile(
            "{\n\t.reg .pred p;\n\t"
            "mbarrier.try_wait.parity.shared::cta.b64 p, [%1], %2;\n\t"
            "selp.u32 %0, 1, 0, p;\n\t}"
            : "=r"(ok) : "r"(bar), "r"(parity) : "memory");
        if (++it > kSpinLimit) __trap();
    } while (!ok);
}
__device__ __forceinline__ bool mbar_try(uint32_t bar, uint32_t parity) {
    uint32_t ok;
    asm volatile(
        "{\n\t.reg .pred p;\n\t"
        "mbarrier.try_wait.parity.shared::cta.b64 p, [%1], %2;\n\t"
        "selp.u32 %0, 1, 0, p;\n\t}"
        : "=r"(ok) : "r"(bar), "r"(parity) : "memory");
    return __all_sync(0xffffffffu, ok);
}
__device__ __forceinline__ void mbar_wait_u(uint32_t bar, uint32_t parity) {
    for (uint32_t it = 0; !mbar_try(bar, parity); it++)
        if (it > kSpinLimit) __trap();
}
__device__ __forceinline__ void tma3d(uint32_t dst, const CUtensorMap* tm, int c0, int c1, int c2, uint32_t bar, uint64_t pol) {
    asm volatile(
        "cp.async.bulk.tensor.3d.shared::cluster.global.mbarrier::complete_tx::bytes.L2::cache_hint "
        "[%0], [%1, {%2, %3, %4}], [%5], %6;"
        ::"r"(dst), "l"(tm), "r"(c0), "r"(c1), "r"(c2), "r"(bar), "l"(pol) : "memory");
}
__device__ __forceinline__ void tma3d_prefetch(const CUtensorMap* tm, int c0, int c1, int c2, uint64_t pol) {
    asm volatile("cp.async.bulk.prefetch.tensor.3d.L2.global.L2::cache_hint [%0, {%1, %2, %3}], %4;"
                 ::"l"(tm), "r"(c0), "r"(c1), "r"(c2), "l"(pol) : "memory");
}
__device__ __forceinline__ uint64_t make_policy(bool keep) {
    uint64_t pol;
    if (keep) asm volatile("createpolicy.fractional.L2::evict_normal.b64 %0, 1.0;" : "=l"(pol));
    else      asm volatile("createpolicy.fractional.L2::evict_first.b64 %0, 1.0;" : "=l"(pol));
    return pol;
}
__device__ __forceinline__ void ldsm4(uint32_t (&r)[4], uint32_t addr) {
    asm volatile("ldmatrix.sync.aligned.m8n8.x4.shared.b16 {%0,%1,%2,%3}, [%4];"
                 : "=r"(r[0]), "=r"(r[1]), "=r"(r[2]), "=r"(r[3]) : "r"(addr) : "memory");
}
__device__ __forceinline__ void ldsm4t(uint32_t (&r)[4], uint32_t addr) {
    asm volatile("ldmatrix.sync.aligned.m8n8.x4.trans.shared.b16 {%0,%1,%2,%3}, [%4];"
                 : "=r"(r[0]), "=r"(r[1]), "=r"(r[2]), "=r"(r[3]) : "r"(addr) : "memory");
}
__device__ __forceinline__ void mma16816(float (&c)[4], const uint32_t (&a)[4], uint32_t b0, uint32_t b1) {
    asm volatile("mma.sync.aligned.m16n8k16.row.col.f32.bf16.bf16.f32 {%0,%1,%2,%3}, {%4,%5,%6,%7}, {%8,%9}, {%0,%1,%2,%3};"
                 : "+f"(c[0]), "+f"(c[1]), "+f"(c[2]), "+f"(c[3])
                 : "r"(a[0]), "r"(a[1]), "r"(a[2]), "r"(a[3]), "r"(b0), "r"(b1));
}
__device__ __forceinline__ float bf16r(float v) { return __bfloat162float(__float2bfloat16_rn(v)); }
__device__ __forceinline__ uint32_t pack_bf16(float lo, float hi) {
    uint32_t r;
    asm("cvt.rn.bf16x2.f32 %0, %1, %2;" : "=r"(r) : "f"(hi), "f"(lo));
    return r;
}
__device__ __forceinline__ bool elect() {
    uint32_t p;
    asm volatile("{\n\t.reg .pred e;\n\telect.sync _|e, 0xffffffff;\n\tselp.u32 %0, 1, 0, e;\n\t}" : "=r"(p));
    return p;
}
__device__ __forceinline__ float fast_sqrt(float v) {
    float r;
    asm("sqrt.approx.f32 %0, %1;" : "=f"(r) : "f"(v));
    return r;
}
__device__ __forceinline__ float ex2(float v) {
    float r;
    asm("ex2.approx.ftz.f32 %0, %1;" : "=f"(r) : "f"(v));
    return r;
}
__device__ __forceinline__ void st_packet(uint4* p, uint32_t a, uint32_t b, uint32_t c, uint32_t tag) {
    asm volatile(
        "{\n\t.reg .b64 lo, hi;\n\t.reg .b128 v;\n\t"
        "mov.b64 lo, {%1, %2};\n\tmov.b64 hi, {%3, %4};\n\tmov.b128 v, {lo, hi};\n\t"
        "st.relaxed.gpu.global.b128 [%0], v;\n\t}"
        ::"l"(p), "r"(a), "r"(b), "r"(c), "r"(tag) : "memory");
}
__device__ __forceinline__ void st_packet(uint4* p, float a, float b, float c, uint32_t tag) {
    st_packet(p, __float_as_uint(a), __float_as_uint(b), __float_as_uint(c), tag);
}
__device__ __forceinline__ uint4 ld_packet(const uint4* p) {
    uint4 v;
    asm volatile(
        "{\n\t.reg .b64 lo, hi;\n\t.reg .b128 v;\n\t"
        "ld.relaxed.gpu.global.b128 v, [%4];\n\t"
        "mov.b128 {lo, hi}, v;\n\tmov.b64 {%0, %1}, lo;\n\tmov.b64 {%2, %3}, hi;\n\t}"
        : "=r"(v.x), "=r"(v.y), "=r"(v.z), "=r"(v.w) : "l"(p) : "memory");
    return v;
}
__device__ __forceinline__ void red_packet(float4* p, float a, float b, float c) {
    asm volatile("red.relaxed.gpu.global.add.v4.f32 [%0], {%1, %2, %3, %4};"
                 ::"l"(p), "f"(a), "f"(b), "f"(c), "f"(1.f) : "memory");
}
#define POLL_UNTIL(pause, loads, done)            \
    for (uint32_t it_ = 0;; it_++) {              \
        loads;                                    \
        if (__all_sync(0xffffffffu, done)) break; \
        if (it_ > kSpinLimit) __trap();           \
        if (pause) __nanosleep(pause);            \
    }
__device__ __forceinline__ uint32_t round24(float v) {
    const uint32_t u = __float_as_uint(v);
    return u + ((u & 0x7f800000u) == 0x7f800000u ? 0u : 0x80u);
}
__device__ __forceinline__ void st_packet5(uint4* p, const float* v, uint32_t tag) {
    const uint32_t r0 = round24(v[0]), r1 = round24(v[1]), r2 = round24(v[2]), r3 = round24(v[3]), r4 = round24(v[4]);
    st_packet(p, __byte_perm(r0, r1, 0x5321), __byte_perm(r1, r2, 0x6532), __byte_perm(r2, r3, 0x7653),
              (r4 >> 8) | (tag << 24));
}
__device__ __forceinline__ void add_packet5(float (&a)[5], const uint4& v) {
    a[0] += __uint_as_float(v.x << 8);
    a[1] += __uint_as_float(__funnelshift_r(v.x, v.y, 16) & 0xffffff00u);
    a[2] += __uint_as_float(__funnelshift_r(v.y, v.z, 8) & 0xffffff00u);
    a[3] += __uint_as_float(v.z & 0xffffff00u);
    a[4] += __uint_as_float(v.w << 8);
}
__device__ __forceinline__ uint32_t now_ns() {
    uint32_t t;
    asm volatile("mov.u32 %0, %globaltimer_lo;" : "=r"(t));
    return t;
}
__device__ __forceinline__ int fresh_lane() {
    int lane = threadIdx.x & 31;
    asm volatile("" : "+r"(lane));
    return lane;
}
__device__ __forceinline__ void pause_ns(uint32_t ns) {
    const uint32_t t0 = now_ns();
    while (now_ns() - t0 < ns) __nanosleep(100);
}
__device__ __forceinline__ float bf_lo(uint32_t v) { return __uint_as_float(v << 16); }
__device__ __forceinline__ float bf_hi(uint32_t v) { return __uint_as_float(v & 0xffff0000u); }
__device__ __forceinline__ float warp_sum(float v) {
#pragma unroll
    for (int o = 16; o > 0; o >>= 1) v += __shfl_xor_sync(0xffffffffu, v, o);
    return v;
}

constexpr float kScale = 0.07216878364870322f * 1.4426950408889634f;

struct Attn {
    float m, l;
    float acc[3][4];
};

__device__ __forceinline__ uint32_t probability(Attn& st, float s) {
    const float e = ex2(s - st.m);
    st.l += e;
    const float hi = bf16r(e);
    const uint32_t hl = pack_bf16(hi, e - hi);
    uint32_t pv;
    asm volatile("movmatrix.sync.aligned.m8n8.trans.b16 %0, %1;" : "=r"(pv) : "r"(hl));
    return pv;
}

__device__ __forceinline__ uint32_t softmax_step(Attn& st, float s) {
    if (__any_sync(0xffffffffu, s > st.m)) {
        float mx = fmaxf(s, __shfl_xor_sync(0xffffffffu, s, 4));
        mx = fmaxf(mx, __shfl_xor_sync(0xffffffffu, mx, 8));
        mx = fmaxf(mx, __shfl_xor_sync(0xffffffffu, mx, 16));
        mx = fmaxf(mx, st.m);
        const float corr = ex2(st.m - mx);
        st.m = mx;
        st.l *= corr;
#pragma unroll
        for (int a = 0; a < 3; a++)
#pragma unroll
            for (int i = 0; i < 4; i++) st.acc[a][i] *= corr;
    }
    return probability(st, s);
}

__global__ void __launch_bounds__(kThreads, 1)
fused_decode_kernel(const __grid_constant__ Params P) {
    extern __shared__ __align__(1024) unsigned char smem[];
    const uint32_t sbase = (uint32_t)__cvta_generic_to_shared(smem);
    const uint32_t sync0 = sbase + kOffSync;
    float* const wbuf = reinterpret_cast<float*>(smem + kOffWbuf);

    const int lane = threadIdx.x & 31;
    const int w = __shfl_sync(0xffffffffu, threadIdx.x >> 5, 0);
    const int cta = blockIdx.x;
    const int h = cta >> 2, jq = cta & 3;

    if (w >= 10) {
        const int i0 = 80 * (w - 10) + lane;
#pragma unroll
        for (int i = 0; i < 3; i++)
            if (i < 2 || lane < 16)
                asm volatile("cp.async.cg.shared.global [%0], [%1], 16;"
                             ::"r"(sbase + kOffWbuf + 16 * (i0 + 32 * i)), "l"(reinterpret_cast<const uint4*>(P.x) + i0 + 32 * i) : "memory");
    }
    if (elect()) {
        if (w == 8) {
#pragma unroll
            for (int i = 0; i < kSlots; i++) {
                mbar_init(sbase + kOffFull + 8 * i, 1);
                mbar_init(sbase + kOffEmpty + 8 * i, 8);
            }
        } else if (w == 9) {
#pragma unroll
            for (int i = 0; i < 10; i++) asm volatile("prefetch.tensormap [%0];" ::"l"(&P.tm[i]) : "memory");
        } else if (w == 10) {
#pragma unroll
            for (int i = 0; i < 14; i++) mbar_init(sync0 + 8 * i, (8 * i == kBarRows || 8 * i >= kBarSentY) ? 8 : 1);
        }
        if (w != 9) asm volatile("fence.mbarrier_init.release.cluster;" ::: "memory");
    }
    __syncwarp();
    if (w == 8) {
        asm volatile("bar.arrive 1, %0;" ::"n"(kThreads) : "memory");
    } else {
        asm volatile("bar.sync 1, %0;" ::"n"(kThreads) : "memory");
    }

    if (w < 8) {
        asm volatile("setmaxnreg.inc.sync.aligned.u32 232;");
        const uint32_t full0 = sbase + kOffFull;
        const uint32_t frag0 = sbase + w * 1024 + (lane & 7) * 128 + (((lane >> 3) ^ (lane & 7)) << 4), frag1 = frag0 ^ 64;
        auto frag_addr = [&](uint32_t s, int k) { return ((k & 1) ? frag1 : frag0) + s * (8 * kSlotBytes) + (k >> 1) * 8192; };
        uint32_t par = 0, rpos = 0, nrows = 0;
        auto wait_tile = [&](uint32_t s) { mbar_wait(full0 + 8 * s, (par >> s) & 1u); };
        auto tile_ready = [&](uint32_t s) { return mbar_test(full0 + 8 * s, (par >> s) & 1u); };
        auto release = [&](uint32_t s) {
            par ^= 1u << s;
            __syncwarp();
            if (elect()) mbar_arrive(full0 + 8 * s + (kOffEmpty - kOffFull));
        };
        auto ring_release = [&]() {
            release(rpos);
            if (++rpos == kRing) rpos = 0;
        };
        auto row_acquire = [&]() { mbar_wait(sync0 + kBarFree, (nrows & 1) ^ 1); };
        auto row_publish = [&]() {
            __syncwarp();
            if (elect()) mbar_arrive(sync0 + kBarRows);
            nrows++;
        };

        uint32_t rf[8][6][4];
#pragma unroll
        for (int i = 0; i < 8; i++)
#pragma unroll
            for (int s = 0; s < 6; s++)
#pragma unroll
                for (int k = 0; k < 4; k++) rf[i][s][k] = 0;

#pragma unroll 1
        for (int pc = 0;; pc++) {
            const uint32_t op = P.prog[pc];
            const uint32_t kind = op & 7u;
            if (kind == OP_END) break;
            const int lane = fresh_lane();
            const int g = lane >> 2, t = lane & 3;
            float* const row = wbuf + w * kWRow;

            if (kind == OP_SEG) {
                const uint32_t b = (op >> 3) & 1u;
                mbar_wait(sync0 + kBarQ + 8 * b, (op >> 4) & 1u);
                const uint2* qf = reinterpret_cast<const uint2*>(smem + kOffQf) + b * 48 + (lane & 7);
                Attn st;
                st.m = -INFINITY; st.l = 0.f;
#pragma unroll
                for (int a = 0; a < 3; a++)
#pragma unroll
                    for (int i = 0; i < 4; i++) st.acc[a][i] = 0.f;

                if (op & (1u << 7)) {
                    float c[4][4] = {};
#pragma unroll
                    for (int k = 0; k < 6; k++) {
                        const uint2 q = qf[8 * k];
#pragma unroll
                        for (int i = 0; i < 4; i++) mma16816(c[i], rf[2 * i][k], q.x, q.y);
                    }
                    float sc[4];
#pragma unroll
                    for (int i = 0; i < 4; i++) sc[i] = (c[i][0] + c[i][3]) * kScale;
                    float mx = fmaxf(fmaxf(sc[0], sc[1]), fmaxf(sc[2], sc[3]));
                    mx = fmaxf(mx, __shfl_xor_sync(0xffffffffu, mx, 4));
                    mx = fmaxf(mx, __shfl_xor_sync(0xffffffffu, mx, 8));
                    st.m = fmaxf(mx, __shfl_xor_sync(0xffffffffu, mx, 16));
                    uint32_t pv[4];
#pragma unroll
                    for (int i = 0; i < 4; i++) pv[i] = probability(st, sc[i]);
#pragma unroll
                    for (int i = 0; i < 4; i++)
#pragma unroll
                        for (int k = 0; k < 6; k++)
                            mma16816(st.acc[k >> 1], rf[2 * i + 1][k], (g >> 1) == 2 * (k & 1) ? pv[i] : 0u,
                                     (g >> 1) == 2 * (k & 1) + 1 ? pv[i] : 0u);
                }

                uint32_t lo = P.prog[pc + 1], hi = P.prog[pc + 2];
                pc += 2;
                bool haveK = false;
#pragma unroll 1
                while (lo & 15u) {
                    const bool rel = lo & 4u;
                    uint32_t sK = kRing - 2 + 2 * (lo & 3u), sV = sK + 1;
                    if (!(lo & 3u)) {
                        sK = rpos;
                        sV = rpos == kRing - 1 ? 0 : rpos + 1;
                        rpos = sV == kRing - 1 ? 0 : sV + 1;
                    }
                    lo = __funnelshift_r(lo, hi, 4);
                    hi >>= 4;
                    if (!haveK) wait_tile(sK);
                    const bool haveV = tile_ready(sV);
                    float c[2][4] = {};
#pragma unroll
                    for (int k = 0; k < 6; k++) {
                        uint32_t a[4];
                        ldsm4(a, frag_addr(sK, k));
                        const uint2 q = qf[8 * k];
                        mma16816(c[k & 1], a, q.x, q.y);
                    }
                    if (rel) release(sK);
                    const uint32_t pv = softmax_step(st, ((c[0][0] + c[0][3]) + (c[1][0] + c[1][3])) * kScale);
                    if (!haveV) wait_tile(sV);
                    haveK = tile_ready((lo & 3u) ? kRing - 2 + 2 * (lo & 3u) : rpos);
#pragma unroll
                    for (int k = 0; k < 6; k++) {
                        uint32_t a[4];
                        ldsm4t(a, frag_addr(sV, k));
                        mma16816(st.acc[k >> 1], a, (g >> 1) == 2 * (k & 1) ? pv : 0u, (g >> 1) == 2 * (k & 1) + 1 ? pv : 0u);
                    }
                    if (rel) release(sV);
                }

                float l = st.l;
                l += __shfl_xor_sync(0xffffffffu, l, 4);
                l += __shfl_xor_sync(0xffffffffu, l, 8);
                l += __shfl_xor_sync(0xffffffffu, l, 16);
                row_acquire();
#pragma unroll
                for (int a = 0; a < 3; a++) {
                    row[64 * a + 16 * t + g] = st.acc[a][0] + st.acc[a][1];
                    row[64 * a + 16 * t + g + 8] = st.acc[a][2] + st.acc[a][3];
                }
                if (lane == 0) { wbuf[8 * kWRow + w] = st.m; wbuf[8 * kWRow + 8 + w] = l; }
                row_publish();
            } else if (kind == OP_RFLOAD) {
#pragma unroll 1
                for (uint32_t tile = (op >> 3) & 7u; tile < (op >> 6); tile++) {
                    wait_tile(rpos);
#pragma unroll
                    for (int i = 0; i < 8; i++) {
                        if (tile == i) {
#pragma unroll
                            for (int k = 0; k < 6; k++) {
                                if (i & 1) ldsm4t(rf[i][k], frag_addr(rpos, k));
                                else ldsm4(rf[i][k], frag_addr(rpos, k));
                            }
                        }
                    }
                    ring_release();
                }
            } else if (kind == OP_QPROJ) {
                const uint32_t mask = (op >> 3) & 3u;
#pragma unroll 1
                for (uint32_t b = 0; b < 2; b++)
                    if ((mask >> b) & 1u) mbar_wait(sync0 + kBarXn + 8 * b, (op >> 5) & 1u);
                const uint32_t bb = mask == 3u ? (g & 1) : (mask >> 1);
                const uint32_t* xs = reinterpret_cast<const uint32_t*>(smem + kOffXn) + bb * 80 + 4 * w + t;
                float acc[3][4] = {};
#pragma unroll 1
                for (int p = 0; p < 3; p++) {
                    wait_tile(rpos);
                    if (p < 2 || w < 4) {
                        const uint32_t xv = xs[32 * p];
                        const uint32_t shrink = p == 2 ? 4096 : 0;
#pragma unroll
                        for (int k = 0; k < 6; k++) {
                            uint32_t a[4];
                            ldsm4t(a, frag_addr(rpos, k) - (k >> 1) * shrink);
                            mma16816(acc[k >> 1], a, (g >> 1) == 2 * (k & 1) ? xv : 0u, (g >> 1) == 2 * (k & 1) + 1 ? xv : 0u);
                        }
                    }
                    ring_release();
                }
#pragma unroll 1
                for (uint32_t b = 0; b < 2; b++) {
                    if (!((mask >> b) & 1u)) continue;
                    row_acquire();
#pragma unroll
                    for (int a = 0; a < 3; a++) {
                        row[64 * a + 16 * t + g] = b ? acc[a][1] : acc[a][0];
                        row[64 * a + 16 * t + g + 8] = b ? acc[a][3] : acc[a][2];
                    }
                    row_publish();
                }
            } else {
                const uint32_t mask = (op >> 3) & 3u;
                const uint32_t bb = mask == 3u ? (g & 1) : (mask >> 1);
                const uint32_t* ob = reinterpret_cast<const uint32_t*>(smem + kOffObf) + bb * 24 + t;
                const uint32_t roff = ((lane & 7) + 8 * (lane >> 4)) * 128 + ((((lane >> 3) & 1) ^ (lane & 7)) << 4);
                uint32_t sl[3];
#pragma unroll
                for (int p = 0; p < 3; p++) {
                    sl[p] = rpos;
                    if (++rpos == kRing) rpos = 0;
                }
                auto frag = [&](uint32_t (&a)[4], int p, int mt) {
                    ldsm4t(a, ((sbase + sl[p] * 8 * kSlotBytes + roff) ^ (((5 * w + mt) & 3) << 5)) + ((5 * w + mt) >> 2) * 2048);
                };
                uint32_t a0[5][4];
                wait_tile(sl[0]);
#pragma unroll
                for (int mt = 0; mt < 5; mt++) frag(a0[mt], 0, mt);
                release(sl[0]);
                wait_tile(sl[1]);
                wait_tile(sl[2]);
                row_acquire();
                if (mask & 1u) mbar_wait(sync0 + kBarO, (op >> 5) & 1u);
                if (mask & 2u) mbar_wait(sync0 + kBarO + 8, (op >> 5) & 1u);
                float c[3][4] = {};
#pragma unroll
                for (int p = 0; p < 3; p++) {
                    const uint32_t b0 = ob[8 * p], b1 = ob[8 * p + 4];
#pragma unroll
                    for (int mt = 0; mt < 5; mt++) {
                        if (p > 0) frag(a0[mt], p, mt);
                        const bool on = (g >> 1) == (mt & 3);
                        mma16816(c[mt == 4 ? 2 : (mt & 1)], a0[mt], on ? b0 : 0u, on ? b1 : 0u);
                    }
                    if (p > 0) release(sl[p]);
                }
                row[16 * t + g] = c[0][0] + c[1][0]; row[80 + 16 * t + g] = c[0][1] + c[1][1];
                row[16 * t + g + 8] = c[0][2] + c[1][2]; row[80 + 16 * t + g + 8] = c[0][3] + c[1][3];
                if (t == 0) {
                    row[64 + g] = c[2][0]; row[144 + g] = c[2][1];
                    row[72 + g] = c[2][2]; row[152 + g] = c[2][3];
                }
                __syncwarp();
                if (lane < 27) {
                    const bool last = ((op >> 5) & 3u) == 3u;
                    float4* dst = (last ? g_out[0][cta % kOutReplicas] : g_acc[0][(op >> 5) & 3u]) + (27 * w + lane) * kAccPad;
                    const float* y = row + 3 * lane;
                    if (mask & 1u) red_packet(dst, y[0], y[1], lane < 26 ? y[2] : 0.f);
                    if (mask & 2u) red_packet(dst + (last ? kOutReplicas : 3) * kAccPad * kAccPackets, y[80], y[81], lane < 26 ? y[82] : 0.f);
                }
                __syncwarp();
                if (lane < 2 && ((mask >> lane) & 1u)) mbar_arrive(sync0 + kBarSentY + 8 * lane);
            }
        }
    } else {
        asm volatile("setmaxnreg.dec.sync.aligned.u32 40;");
        if (w == 8) {
            if (elect()) {
#pragma unroll
                for (int p = 0; p < kRing; p++) {
                    const CUtensorMap* tm = &P.tm[p == 2 ? 8 : 4];
                    mbar_expect(sbase + kOffFull + 8 * p, p == 2 ? 4 * kSlotBytes : 8 * kSlotBytes);
                    tma3d(sbase + p * 8 * kSlotBytes, tm, 0, 160 * jq + 64 * p, 3 * h, sbase + kOffFull + 8 * p, make_policy(false));
                    tma3d_prefetch(tm, 0, 160 * jq + 64 * p, 3 * h, make_policy(true));
                }
            }
            __syncwarp();
            const int rowA = h * 4096 + 3072 + 256 * jq, rowB = h * 4096 + 1024 * jq;
            const int rowWq = 160 * jq, rowWo = 192 * h + 48 * jq;
            uint32_t credit = kCredit, na = 0;
            const uint64_t polKeep = make_policy(true), polStream = make_policy(false);
            uint32_t fifo = 0x012u, queued = 7u, stale = 0, par = 7u, nfl = kRing, next = now_ns() + kStartDelay;
            auto coord = [&](uint32_t e) {
                return (int)((e >> 10) & 0x3ffffu) + ((e & 4u) ? ((e & 2u) ? rowWo : rowWq) : ((e & 2u) ? rowB : rowA));
            };
            auto interval = [&](uint32_t e) {
                return (e & 6u) == 6u ? kTauWo : ((e & LD_HANDOFF) ? kTauHandoff : kTau) >> ((e >> 28) & 1u);
            };
            auto map = [&](uint32_t e) { return &P.tm[(e & 7u) + ((e >> 26) & 4u)]; };
            uint32_t latest = 2;
            auto slot_free = [&](uint32_t s) { return mbar_test(sbase + kOffEmpty + 8 * s, ((par >> s) & 1u) ^ 1u); };
            auto landed = [&](uint32_t s) { return mbar_test(sbase + kOffFull + 8 * s, ((par >> s) & 1u) ^ 1u); };
            auto load = [&](uint32_t e, bool counted) {
                const uint32_t s = (e >> 4) & 15u;
                const int c1 = coord(e), c2 = ((e >> 1) & 3u) == 2u ? 3 * h : 0;
                if (elect()) {
                    mbar_expect(sbase + kOffFull + 8 * s, (e & 6u) == 6u ? 20480 : (8 * kSlotBytes) >> ((e >> 28) & 1u));
                    tma3d(sbase + s * 8 * kSlotBytes, map(e), 0, c1, c2, sbase + kOffFull + 8 * s, polStream);
                    if (e & LD_KEEP) tma3d_prefetch(map(e), 0, c1, c2, polKeep);
                }
                if (counted) {
                    fifo = (fifo << 4) | s;
                    queued |= 1u << s;
                    nfl++;
                    latest = s;
                }
                par ^= 1u << s;
            };
            uint32_t m = 0, pfd = 0;
#pragma unroll 1
            for (uint32_t n = kRing;; n++) {
                const uint32_t e = P.loads[n];
                if (!(e & LD_VALID)) break;
                const uint32_t s = (e >> 4) & 15u;
                if (m < n) m = n;
                const uint32_t look = (e & LD_FAR) ? kLookFar : kLook;
                for (uint32_t it = 0; !slot_free(s); it++) {
                    if (it > 16 * kSpinLimit) __trap();
                    const uint32_t f = P.loads[m];
                    if (m >= n + look || !(f & LD_VALID)) continue;
                    if (f & LD_HIT) { m++; continue; }
                    const uint32_t now = now_ns();
                    if ((int)(now - next) >= 0 && landed(latest)) {
                        if (elect()) tma3d_prefetch(map(f), 0, coord(f), ((f >> 1) & 3u) == 2u ? 3 * h : 0, polStream);
                        next = now + interval(f);
                        pfd |= 1u << (m & 31u);
                        m++;
                    }
                }
                stale |= queued & (1u << s);
                queued &= ~(1u << s);
                if (e & LD_ANCHOR) {
                    const uint32_t t0 = __shfl_sync(0xffffffffu, *reinterpret_cast<volatile uint32_t*>(smem + kOffAnchor), 0) + P.anchorDelay[na];
                    if (m <= n || (int)(t0 - next) > 0) next = t0;
                    credit = P.anchorCredit[na++];
                }
                const bool counted = !(e & LD_HIT) && !((pfd >> (n & 31u)) & 1u);
                pfd &= ~(1u << (n & 31u));
                if (counted) {
                    for (const uint32_t win = n < kStartLoads ? kStartWindow : kWindow; nfl >= win; nfl--) {
                        const uint32_t o = (fifo >> (4 * nfl - 4)) & 15u;
                        if ((stale >> o) & 1u) {
                            stale ^= 1u << o;
                        } else {
                            mbar_wait_u(sbase + kOffFull + 8 * o, ((par >> o) & 1u) ^ 1u);
                            queued ^= 1u << o;
                        }
                    }
                    uint32_t now = now_ns();
                    while ((int)(now - next) < 0) now = now_ns();
                    if ((int)(now - credit - next) > 0) next = now - credit;
                    next += interval(e);
                }
                load(e, counted);
            }
        } else {
            if (w == 9) {
#pragma unroll 1
                for (int n = 0;; n++) {
                    const uint32_t job = P.merge[n];
                    if ((job & 3u) == MG_END) break;
                    const uint32_t b = (job >> 2) & 1u;
                    const uint32_t tag = 1 + ((job >> 3) & 3u);
                    mbar_wait(sync0 + kBarRows, n & 1);
                    if ((job & 3u) == MG_Q) {
                        float o[5] = {}, e[5] = {};
                        const float* ext = wbuf + 2 * (lane & 3) * kWRow + 5 * min(32 + (lane >> 2), 38);
#pragma unroll
                        for (int k = 0; k < 5; k++) e[k] = ext[k] + ext[kWRow + k];
#pragma unroll
                        for (int i = 0; i < 8; i++)
#pragma unroll
                            for (int k = 0; k < 5; k++) o[k] += wbuf[i * kWRow + 5 * lane + k];
                        st_packet5(&g_q[b][h][jq][lane], o, tag);
#pragma unroll
                        for (int k = 0; k < 5; k++) {
                            e[k] += __shfl_xor_sync(0xffffffffu, e[k], 1);
                            e[k] += __shfl_xor_sync(0xffffffffu, e[k], 2);
                        }
                        if ((lane & 3) == 0) st_packet5(&g_q[b][h][jq][32 + (lane >> 2)], e, tag);
                        __syncwarp();
                        if (lane == 0) mbar_arrive(sync0 + kBarSentQ + 8 * b);
                    } else {
                        float2* cp = reinterpret_cast<float2*>(smem + kOffCpart) + b * (kWRow / 2) + 3 * lane;
                        float2* cml = reinterpret_cast<float2*>(smem + kOffMl + 64) + b;
                        const float4* ml = reinterpret_cast<const float4*>(smem + kOffMl);
                        const bool merge = !(job & 32u);
                        const float2 pml = merge ? *cml : make_float2(-INFINITY, 0.f);
                        const float4 m0 = ml[0], m1 = ml[1];
                        float sc[8] = {m0.x, m0.y, m0.z, m0.w, m1.x, m1.y, m1.z, m1.w};
                        const float M = fmaxf(fmaxf(fmaxf(fmaxf(sc[0], sc[1]), fmaxf(sc[2], sc[3])),
                                                    fmaxf(fmaxf(sc[4], sc[5]), fmaxf(sc[6], sc[7]))), pml.x);
#pragma unroll
                        for (int i = 0; i < 8; i++) sc[i] = ex2(sc[i] - M);
                        const float ps = ex2(pml.x - M);
                        float2 o[3];
#pragma unroll
                        for (int k = 0; k < 3; k++) {
                            o[k] = merge ? cp[k] : make_float2(0.f, 0.f);
                            o[k].x *= ps; o[k].y *= ps;
                        }
#pragma unroll
                        for (int i = 0; i < 8; i++)
#pragma unroll
                            for (int k = 0; k < 3; k++) {
                                const float2 v = reinterpret_cast<const float2*>(wbuf)[i * (kWRow / 2) + 3 * lane + k];
                                o[k].x = fmaf(v.x, sc[i], o[k].x);
                                o[k].y = fmaf(v.y, sc[i], o[k].y);
                            }
                        const float4 l0 = ml[2], l1 = ml[3];
                        const float L = fmaf(pml.y, ps, ((l0.x * sc[0] + l0.y * sc[1]) + (l0.z * sc[2] + l0.w * sc[3])) +
                                                        ((l1.x * sc[4] + l1.y * sc[5]) + (l1.z * sc[6] + l1.w * sc[7])));
                        if (job & 64u) {
                            uint4* dst = &g_p[b][h][lane >> 3][jq][2 * (lane & 7)];
                            st_packet(dst, o[0].x, o[0].y, o[1].x, tag);
                            st_packet(dst + 1, o[1].y, o[2].x, o[2].y, tag);
                            if (lane < 8) st_packet(&g_p[b][h][lane >> 1][jq][16 + (lane & 1)], M, L, 0.f, tag);
                            if (lane == 0) mbar_arrive(sync0 + kBarSentP + 8 * b);
                        } else {
#pragma unroll
                            for (int k = 0; k < 3; k++) cp[k] = o[k];
                            __syncwarp();
                            if (lane == 0) *cml = make_float2(M, L);
                        }
                    }
                    __syncwarp();
                    if (lane == 0) mbar_arrive(sync0 + kBarFree);
                }
            } else {
                const uint32_t b = w - 10;
                __nv_bfloat16* const xn = reinterpret_cast<__nv_bfloat16*>(smem + kOffXn) + b * 160;
                __nv_bfloat16* const qd = reinterpret_cast<__nv_bfloat16*>(smem + kOffQf) + b * 192;
                __nv_bfloat16* const ob = reinterpret_cast<__nv_bfloat16*>(smem + kOffObf) + b * 48;
                uint2* const own = reinterpret_cast<uint2*>(smem + kOffOwn) + 2 * b;
#pragma unroll 1
                for (uint32_t layer = 0; layer < 4; layer++) {
                    const uint32_t tag = layer + 1;
                    {
                        int lane = fresh_lane();
                        uint32_t x01[7], x2[7];
                        if (layer == 0) {
                            const uint4* stage = reinterpret_cast<const uint4*>(wbuf) + 80 * b;
                            asm volatile("cp.async.wait_all;" ::: "memory");
                            __syncwarp();
#pragma unroll
                            for (int i = 0; i < 7; i++) {
                                const int p = lane + 32 * i, u = p % 27;
                                const unsigned short* xp = reinterpret_cast<const unsigned short*>(stage) + (p / 27) * 80 + 3 * u;
                                x01[i] = p < kAccPackets ? xp[0] | ((uint32_t)xp[1] << 16) : 0u;
                                x2[i] = (p < kAccPackets && u < 26) ? xp[2] : 0u;
                            }
                        } else {
                            mbar_wait(sync0 + kBarSentY + 8 * b, (layer - 1) & 1);
                            pause_ns(kDelayX);
                            uint4 v[7];
                            const uint4* src = reinterpret_cast<const uint4*>(&g_acc[b][layer - 1][lane * kAccPad]);
                            const uint32_t done = __float_as_uint(kAccDone);
                            POLL_UNTIL(kPauseX, v[0] = ld_packet(src + (27 * (cta & 7) + min(lane, 26) - lane) * kAccPad), v[0].w == done);
                            POLL_UNTIL(kPauseX,
                                v[0] = ld_packet(src); v[1] = ld_packet(src + 32 * kAccPad); v[2] = ld_packet(src + 64 * kAccPad);
                                v[3] = ld_packet(src + 96 * kAccPad); v[4] = ld_packet(src + 128 * kAccPad);
                                v[5] = ld_packet(src + 160 * kAccPad); v[6] = ld_packet(src + (lane < 24 ? 192 * kAccPad : 0)),
                                v[0].w == done && v[1].w == done && v[2].w == done && v[3].w == done && v[4].w == done &&
                                    v[5].w == done && v[6].w == done);
#pragma unroll
                            for (int i = 0; i < 7; i++) {
                                x01[i] = pack_bf16(__uint_as_float(v[i].x), __uint_as_float(v[i].y));
                                x2[i] = pack_bf16(__uint_as_float(v[i].z), 0.f);
                            }
                            if (lane >= 24) x01[6] = x2[6] = 0u;
                        }
#pragma unroll
                        for (int i = 0; i < 7; i++) {
                            const int p = lane + 32 * i;
                            if ((p & 127) == cta && p < kAccPackets) {
                                own[i >> 2] = make_uint2(x01[i], x2[i]);
                            }
                        }
                        float sum = 0.f;
#pragma unroll
                        for (int i = 0; i < 7; i++) sum += (bf_lo(x01[i]) + bf_hi(x01[i])) + bf_lo(x2[i]);
                        const float mean = warp_sum(sum) * (1.f / 640.f);
                        float sq = 0.f;
#pragma unroll
                        for (int i = 0; i < 7; i++) {
                            const bool none = i == 6 && lane >= 24;
                            const float d0 = none ? 0.f : bf_lo(x01[i]) - mean, d1 = none ? 0.f : bf_hi(x01[i]) - mean;
                            const bool last = lane == 26 - 5 * i || lane == 53 - 5 * i;
                            const float d2 = (none || last) ? 0.f : bf_lo(x2[i]) - mean;
                            sq += fmaf(d0, d0, fmaf(d1, d1, d2 * d2));
                        }
                        const float var = warp_sum(sq) * (1.f / 640.f);
                        const float meanb = bf16r(mean);
                        const float rden = __fdividef(1.f, bf16r(fast_sqrt(bf16r(bf16r(var) + 1e-5f))));
#pragma unroll
                        for (int i = 0; i < 7; i++) {
                            const uint32_t q = lane + 32 * i - 54 * jq;
                            if (q < 54u) {
                                const int c = 3 * q - (q >= 27u);
                                xn[c] = __float2bfloat16_rn(bf16r(bf_lo(x01[i]) - meanb) * rden);
                                xn[c + 1] = __float2bfloat16_rn(bf16r(bf_hi(x01[i]) - meanb) * rden);
                                if (q != 26u && q != 53u) xn[c + 2] = __float2bfloat16_rn(bf16r(bf_lo(x2[i]) - meanb) * rden);
                            }
                        }
                        if (lane == 0) *reinterpret_cast<volatile uint32_t*>(smem + kOffAnchor) = now_ns();
                        __syncwarp();
                        if (lane == 0) mbar_arrive(sync0 + kBarXn + 8 * b);
                        if (layer >= 2 && lane < 4 && cta + 128 * (lane >> 1) < kAccPackets)
                            g_acc[b][layer - 2][(cta + 128 * (lane >> 1)) * kAccPad + (lane & 1)] = make_float4(0.f, 0.f, 0.f, 0.f);
                        __syncwarp();
                    }
                    {
                        const int lane = fresh_lane();
                        mbar_wait(sync0 + kBarSentQ + 8 * b, layer & 1);
                        if (layer == 0 || (layer == 1 && b == 1)) pause_ns(kDelayIdle);
                        uint4 v[5];
                        const uint4* src = &g_q[b][h][0][lane];
                        const uint4* ext = &g_q[b][h][lane & 3][lane < 28 ? 32 + (lane >> 2) : 38];
                        POLL_UNTIL(0,
                            v[0] = ld_packet(src); v[1] = ld_packet(src + 40); v[2] = ld_packet(src + 80);
                            v[3] = ld_packet(src + 120); v[4] = ld_packet(ext),
                            (v[0].w >> 24) == tag && (v[1].w >> 24) == tag && (v[2].w >> 24) == tag &&
                                (v[3].w >> 24) == tag && (v[4].w >> 24) == tag);
                        __syncwarp();
                        auto store_q = [&](int d, float q) {
                            qd[(d & ~31) + ((d >> 3) & 1) * 16 + ((d >> 1) & 3) * 4 + ((d >> 4) & 1) * 2 + (d & 1)] =
                                __float2bfloat16_rn(q);
                        };
                        float a[5] = {};
#pragma unroll
                        for (int i = 0; i < 4; i++) add_packet5(a, v[i]);
#pragma unroll
                        for (int k = 0; k < 5; k++) store_q(5 * lane + k, a[k]);
                        float e[5] = {};
                        add_packet5(e, v[4]);
#pragma unroll
                        for (int k = 0; k < 5; k++) {
                            e[k] += __shfl_xor_sync(0xffffffffu, e[k], 1);
                            e[k] += __shfl_xor_sync(0xffffffffu, e[k], 2);
                            const int d = 160 + 5 * (lane >> 2) + k;
                            if ((lane & 3) == 0 && d < 192) store_q(d, e[k]);
                        }
                        __syncwarp();
                        if (lane == 0) mbar_arrive(sync0 + kBarQ + 8 * b);
                    }
                    {
                        const int lane = fresh_lane();
                        mbar_wait(sync0 + kBarSentP + 8 * b, layer & 1);
                        pause_ns((b == 0 && (layer == 0 || layer == 3)) ? kDelayIdle : (layer == 3 ? 0 : kDelayP));
                        uint4 v0, v1, ml;
                        const uint4* src = &g_p[b][h][jq][2 * (lane >> 4)][lane & 15];
                        const uint4* mls = &g_p[b][h][jq][lane & 3][16];
                        POLL_UNTIL(0, v0 = ld_packet(src); v1 = ld_packet(src + 18); ml = ld_packet(mls),
                                   v0.w == tag && v1.w == tag && ml.w == tag);
                        __syncwarp();
                        const float mi = __uint_as_float(ml.x);
                        float M = fmaxf(mi, __shfl_xor_sync(0xffffffffu, mi, 1));
                        M = fmaxf(M, __shfl_xor_sync(0xffffffffu, M, 2));
                        const float sc = ex2(mi - M);
                        float L = __uint_as_float(ml.y) * sc;
                        L += __shfl_xor_sync(0xffffffffu, L, 1);
                        L += __shfl_xor_sync(0xffffffffu, L, 2);
                        const float s0 = __shfl_sync(0xffffffffu, sc, 2 * (lane >> 4));
                        const float s1 = __shfl_sync(0xffffffffu, sc, 2 * (lane >> 4) + 1);
                        float o0 = fmaf(__uint_as_float(v0.x), s0, __uint_as_float(v1.x) * s1);
                        float o1 = fmaf(__uint_as_float(v0.y), s0, __uint_as_float(v1.y) * s1);
                        float o2 = fmaf(__uint_as_float(v0.z), s0, __uint_as_float(v1.z) * s1);
                        o0 += __shfl_xor_sync(0xffffffffu, o0, 16);
                        o1 += __shfl_xor_sync(0xffffffffu, o1, 16);
                        o2 += __shfl_xor_sync(0xffffffffu, o2, 16);
                        if (lane < 16) {
                            ob[3 * lane] = __float2bfloat16_rn(__fdividef(o0, L));
                            ob[3 * lane + 1] = __float2bfloat16_rn(__fdividef(o1, L));
                            ob[3 * lane + 2] = __float2bfloat16_rn(__fdividef(o2, L));
                        }
                        __syncwarp();
                        if (lane == 0) mbar_arrive(sync0 + kBarO + 8 * b);
                        const int p = cta + 128 * lane;
                        if (p < kAccPackets) {
                            const uint2 v = own[lane];
                            red_packet((layer == 3 ? g_out[b][0] : g_acc[b][layer]) + p * kAccPad, bf_lo(v.x), bf_hi(v.x), bf_lo(v.y));
                        }
                    }
                }
                {
                    mbar_wait(sync0 + kBarSentY + 8 * b, 1);
                    const int p = cta + 128 * ((lane / kOutReplicas) & 1), r = lane % kOutReplicas;
                    float4* src = &g_out[b][r][(p < kAccPackets ? p : cta) * kAccPad];
                    const float want = kCtas / kOutReplicas + (r == 0);
                    uint4 v;
                    for (uint32_t it = 0;; it++) {
                        v = ld_packet(reinterpret_cast<const uint4*>(src));
                        if (__all_sync(0xffffffffu, v.w == __float_as_uint(want))) break;
                        if (it > kSpinLimit) __trap();
                    }
                    float o0 = __uint_as_float(v.x), o1 = __uint_as_float(v.y), o2 = __uint_as_float(v.z);
#pragma unroll
                    for (int o = 1; o < kOutReplicas; o <<= 1) {
                        o0 += __shfl_xor_sync(0xffffffffu, o0, o);
                        o1 += __shfl_xor_sync(0xffffffffu, o1, o);
                        o2 += __shfl_xor_sync(0xffffffffu, o2, o);
                    }
                    if (lane < 2 * kOutReplicas && p < kAccPackets) {
                        if (r < 3 - (p % 27 == 26))
                            P.out[b * 640 + (p / 27) * 80 + 3 * (p % 27) + r] = __float2bfloat16_rn(r == 0 ? o0 : r == 1 ? o1 : o2);
                        *src = make_float4(0.f, 0.f, 0.f, 0.f);
                        if (r == 0) g_acc[b][2][p * kAccPad] = make_float4(0.f, 0.f, 0.f, 0.f);
                    }
                }
            }
        }
    }
}


struct Sched {
    Params& P;
    int np = 0, nm = 0, nl = 0, rslot = 0, mark = 0;
    uint32_t pending = 0;
    enum { RF = 1 << 7, FIRST = 1 << 11, PUB = 1 << 12 };

    void handoff_begin() { mark = nl; }
    void handoff_end() { for (int i = mark; i < nl; i++) P.loads[i] |= LD_HANDOFF; }
    void slot(uint32_t e, int s) { P.loads[nl++] = e | (s << 4); }
    void ring(uint32_t e) {
        slot(e | pending, rslot);
        pending = 0;
        rslot = (rslot + 1) % kRing;
    }
    static uint32_t tile(int isB, int b, int idx, int v) {
        return LD_VALID | (2 * isB + v) | (uint32_t)(b * 32 * 4096 + 64 * idx) << 10;
    }
    void pair(int isB, int b, int idx, uint32_t fk = 0, uint32_t fv = 0) {
        ring(tile(isB, b, idx, 0) | fk);
        ring(tile(isB, b, idx, 1) | fv);
    }
    void qproj(int mask, int layer, uint32_t f) {
        for (int p = 0; p < 3; p++) ring(LD_VALID | (4 + (layer & 1)) | (64 * p) << 10 | (p == 2 ? LD_HALF : 0u) | f);
        if (layer > 0) pending = LD_ANCHOR;
        P.prog[np++] = OP_QPROJ | (mask << 3) | (layer << 5);
        for (int b = 0; b < 2; b++)
            if ((mask >> b) & 1) P.merge[nm++] = MG_Q | (b << 2) | (layer << 3);
    }
    void oproj(int mask, int layer, uint32_t fLast) {
        for (int p = 0; p < 3; p++) ring(LD_VALID | (6 + (layer & 1)) | (16 * p) << 10 | (p == 2 ? fLast : 0u));
        P.prog[np++] = OP_OPROJ | (mask << 3) | (layer << 5);
    }
    void rfload(int from, int to, int isB, int b, int idx0) {
        for (int i = from; i < to; i++) ring(tile(isB, b, idx0 + i / 2, i & 1));
        P.prog[np++] = OP_RFLOAD | (from << 3) | (to << 6);
    }
    void seg(int b, int layer, uint32_t flags, const char* order) {
        uint64_t list = 0;
        for (int n = 0; order[n]; n++) {
            const char c = order[n];
            uint64_t item = 12;
            if (c >= 'a' && c <= 'c') item = 12 | (c - 'a' + 1);
            if (c >= 'A' && c <= 'C') item = 8 | (c - 'A' + 1);
            list |= item << (4 * n);
        }
        P.prog[np++] = OP_SEG | (b << 3) | ((layer & 1) << 4) | (flags & RF);
        P.prog[np++] = (uint32_t)list;
        P.prog[np++] = (uint32_t)(list >> 32);
        P.merge[nm++] = MG_ATTN | (b << 2) | (layer << 3) | ((flags & FIRST) ? 32 : 0) | ((flags & PUB) ? 64 : 0);
    }
};

void build_schedule(Params& P) {
    for (int i = 0; i < kMaxProg; i++) P.prog[i] = OP_END;
    for (int i = 0; i < kMaxMerge; i++) P.merge[i] = MG_END;
    for (int i = 0; i < kMaxLoads; i++) P.loads[i] = 0;
    const uint32_t anchorDelay[kAnchors] = {200, 200, 200, 200, 0};
    const uint32_t anchorCredit[kAnchors] = {kCredit, 2500, 2500, kCredit, 300};
    for (int i = 0; i < kAnchors; i++) {
        P.anchorDelay[i] = anchorDelay[i];
        P.anchorCredit[i] = anchorCredit[i];
    }

    Sched S{P};
    using F = Sched;
    const int keep[2] = {9, 10};
    auto kept = [&](int b, int idx, int v, uint32_t f) { return (2 * (15 - idx) + (1 - v)) < keep[b] ? f : 0u; };
    int nextD[2] = {3, 7}, nextH[2] = {11, 11}, nextK = 11;
    auto fill = [&](int b, int layer, int n, uint32_t flags = 0) {
        for (int i = 0; i < n; i++) S.pair(1, b, nextD[b]++);
        S.seg(b, layer, flags, &"dd"[2 - n]);
    };
    auto mixed = [&](int b, int layer, uint32_t flags, const char* order, int refill0, const int* pos) {
        int tiles = 0, done = 0, dst[6], n = 0;
        for (const char* c = order; *c; c++)
            if (*c >= 'a' && *c <= 'c') { dst[n++] = kRing + 2 * (*c - 'a'); dst[n++] = kRing + 2 * (*c - 'a') + 1; }
        for (const char* c = order; *c; c++) {
            if (*c != 'h' && *c != 'd' && *c != 'k') continue;
            const int idx = *c == 'h' ? nextH[b]++ : *c == 'k' ? nextK++ : nextD[b]++;
            for (int v = 0; v < 2; v++, tiles++) {
                for (; done < n && pos[done] <= tiles; done++) S.slot(F::tile(1, 1, refill0 + done / 2, done & 1) | LD_FAR, dst[done]);
                S.ring(F::tile(1, b, idx, v) | LD_FAR | kept(b, idx, v, *c == 'h' ? LD_HIT : *c == 'k' ? LD_KEEP : 0u));
            }
        }
        S.seg(b, layer, flags, order);
    };

    S.qproj(3, 0, LD_KEEP);
    S.slot(F::tile(0, 1, 0, 0), kRing);
    S.slot(F::tile(0, 1, 0, 1), kRing + 1);
    S.rfload(0, 8, 0, 0, 0);
    S.seg(0, 0, F::RF | F::FIRST | F::PUB, "");
    S.handoff_begin();
    for (int i = 1; i < 4; i++) S.pair(0, 1, i);
    S.seg(1, 0, F::FIRST | F::PUB, "addd");
    S.oproj(3, 0, LD_KEEP);
    for (int i = 0; i < 4; i++) S.slot(F::tile(1, 0, i / 2, i & 1), kRing + i);
    S.qproj(3, 1, LD_KEEP);
    for (int i = 4; i < 6; i++) S.slot(F::tile(1, 0, i / 2, i & 1), kRing + i);
    S.handoff_end();
    for (int i = 3; i < 16; i++) S.pair(1, 0, i, kept(0, i, 0, LD_KEEP), kept(0, i, 1, LD_KEEP));
    S.seg(0, 1, F::FIRST | F::PUB, "dddAdddBdddCdddd");
    S.handoff_begin();
    S.oproj(1, 1, 0);
    fill(1, 1, 2, F::FIRST);
    S.qproj(1, 2, LD_HIT);
    fill(1, 1, 1);
    S.seg(0, 2, F::RF | F::FIRST | F::PUB, "");
    S.rfload(0, 2, 1, 1, 3);
    S.oproj(1, 2, LD_HIT);
    S.rfload(2, 6, 1, 1, 3);
    fill(1, 1, 1);
    S.qproj(1, 3, LD_HIT);
    S.rfload(6, 8, 1, 1, 3);
    S.handoff_end();
    const int pos4[6] = {3, 3, 4, 5, 7, 7};
    mixed(0, 3, F::FIRST, "ahbchhhh", 0, pos4);
    mixed(1, 1, F::RF | F::PUB, "kkkAkBCk", 0, nullptr);
    S.handoff_begin();
    S.oproj(2, 1, LD_KEEP);
    fill(0, 3, 2);
    S.qproj(2, 2, 0);
    fill(0, 3, 1);
    for (int i = 0; i < 4; i++) S.pair(0, 1, i);
    S.seg(1, 2, F::FIRST | F::PUB, "dddd");
    fill(0, 3, 1);
    S.oproj(2, 2, 0);
    fill(0, 3, 2);
    S.qproj(2, 3, 0);
    S.handoff_end();
    mixed(0, 3, F::PUB, "dd", 0, nullptr);
    const int pos6[6] = {3, 3, 5, 8, 9, 10};
    nextD[1] = 10;
    mixed(1, 3, F::RF | F::FIRST | F::PUB, "adbhchhAhBhC", 7, pos6);
    S.oproj(3, 3, LD_HIT);
}

typedef CUresult (*EncodeFn)(CUtensorMap*, CUtensorMapDataType, cuuint32_t, void*, const cuuint64_t*,
                             const cuuint64_t*, const cuuint32_t*, const cuuint32_t*, CUtensorMapInterleave,
                             CUtensorMapSwizzle, CUtensorMapL2promotion, CUtensorMapFloatOOBfill);

}

extern "C" void kernel_launch(void* const* d_in, const int* in_sizes, int n_in, void* d_out, int out_size) {
    (void)in_sizes; (void)n_in; (void)out_size;
    Params P;
    void* fn = nullptr;
    cudaDriverEntryPointQueryResult qr;
    cudaGetDriverEntryPoint("cuTensorMapEncodeTiled", &fn, cudaEnableDefault, &qr);
    EncodeFn encode = reinterpret_cast<EncodeFn>(fn);
    auto make_map = [&](int i, void* base, cuuint64_t rows, cuuint64_t rowBytes, cuuint64_t lines, cuuint32_t boxRows,
                        cuuint32_t boxLines) {
        const cuuint64_t dims[3] = {64, rows, lines};
        const cuuint64_t strides[2] = {rowBytes, 128};
        const cuuint32_t box[3] = {64, boxRows, boxLines};
        const cuuint32_t es[3] = {1, 1, 1};
        encode(&P.tm[i], CU_TENSOR_MAP_DATA_TYPE_BFLOAT16, 3, base, dims, strides, box, es, CU_TENSOR_MAP_INTERLEAVE_NONE,
               CU_TENSOR_MAP_SWIZZLE_128B, CU_TENSOR_MAP_L2_PROMOTION_NONE, CU_TENSOR_MAP_FLOAT_OOB_FILL_NONE);
    };
    for (int i = 0; i < 2; i++) {
        void* const* in = d_in + 5 * i;
        make_map(2 * i, in[1], 2 * 32 * 4096, 384, 3, 64, 3);
        make_map(2 * i + 1, in[2], 2 * 32 * 4096, 384, 3, 64, 3);
        make_map(4 + i, in[3], 640, 12288, 96, 64, 3);
        make_map(8 + i, in[3], 640, 12288, 96, 32, 3);
        make_map(6 + i, in[4], 6144, 1280, 10, 16, 10);
    }
    P.x = static_cast<const __nv_bfloat16*>(d_in[0]);
    P.out = static_cast<__nv_bfloat16*>(d_out);
    build_schedule(P);
    cudaFuncSetAttribute(fused_decode_kernel, cudaFuncAttributeMaxDynamicSharedMemorySize, kSmemBytes);
    fused_decode_kernel<<<kCtas, kThreads, kSmemBytes>>>(P);
}
```

```cpp
#include <cuda_runtime.h>
#include <cuda_bf16.h>
#include <cuda.h>
#include <stdint.h>

namespace {

constexpr int kCtas = 128;
constexpr int kThreads = 384;
constexpr int kSlotBytes = 3072;
constexpr int kRing = 3;
constexpr int kSlots = 9;
constexpr int kWRow = 192;

constexpr int kOffWbuf = kSlots * 8 * kSlotBytes;
constexpr int kOffMl = kOffWbuf + 8 * kWRow * 4;
constexpr int kOffCpart = kOffMl + 20 * 4;
constexpr int kOffQf = kOffCpart + 2 * kWRow * 4;
constexpr int kOffXn = kOffQf + 2 * 96 * 4;
constexpr int kOffObf = kOffXn + 2 * 160 * 2;
constexpr int kOffFull = kOffObf + 2 * 48 * 2;
constexpr int kOffEmpty = kOffFull + kSlots * 8;
constexpr int kOffSync = kOffEmpty + kSlots * 8;
constexpr int kOffAnchor = kOffSync + 14 * 8;
constexpr int kOffOwn = kOffAnchor + 8;
constexpr int kSmemBytes = kOffOwn + 32;
static_assert(kSmemBytes <= 232448, "shared memory budget");
constexpr int kBarRows = 0, kBarFree = 8, kBarQ = 16, kBarXn = 32, kBarO = 48;
constexpr int kBarSentQ = 64, kBarSentP = 80, kBarSentY = 96;

constexpr int kMaxProg = 72;
constexpr int kMaxMerge = 32;
constexpr int kMaxLoads = 176;
constexpr int kAnchors = 5;

constexpr uint32_t kTau = 970;
constexpr uint32_t kTauHandoff = 1000;
constexpr uint32_t kTauWo = 833;
constexpr uint32_t kCredit = 700;
constexpr uint32_t kWindow = 3;
constexpr uint32_t kStartWindow = 4, kStartLoads = 10, kStartDelay = 1000;
constexpr uint32_t kLook = 3, kLookFar = 4;
constexpr uint32_t kDelayX = 2200, kDelayP = 1000, kDelayIdle = 3500, kPauseX = 200;

enum : uint32_t { OP_END = 0, OP_QPROJ = 1, OP_RFLOAD = 2, OP_SEG = 3, OP_OPROJ = 4 };
enum : uint32_t { MG_END = 0, MG_ATTN = 1, MG_Q = 2 };
enum : uint32_t {
    LD_KEEP = 1u << 3,
    LD_HANDOFF = 1u << 8,
    LD_VALID = 1u << 9,
    LD_HALF = 1u << 28,
    LD_ANCHOR = 1u << 29,
    LD_FAR = 1u << 30,
    LD_HIT = 1u << 31
};

struct alignas(64) Params {
    CUtensorMap tm[10];
    const __nv_bfloat16* x;
    __nv_bfloat16* out;
    uint32_t anchorDelay[kAnchors], anchorCredit[kAnchors];
    uint32_t prog[kMaxProg];
    uint32_t merge[kMaxMerge];
    uint32_t loads[kMaxLoads];
};

__device__ uint4 g_q[2][32][4][40];
__device__ uint4 g_p[2][32][4][4][18];
constexpr int kAccPackets = 216;
constexpr float kAccDone = 129.f;
constexpr int kAccPad = 2;
__device__ float4 g_acc[2][3][kAccPackets * kAccPad];
constexpr int kOutReplicas = 8;
__device__ float4 g_out[2][kOutReplicas][kAccPackets * kAccPad];

constexpr uint32_t kSpinLimit = 1u << 22;

__device__ __forceinline__ void mbar_init(uint32_t bar, uint32_t count) {
    asm volatile("mbarrier.init.shared::cta.b64 [%0], %1;" ::"r"(bar), "r"(count) : "memory");
}
__device__ __forceinline__ void mbar_arrive(uint32_t bar) {
    asm volatile("mbarrier.arrive.shared::cta.b64 _, [%0];" ::"r"(bar) : "memory");
}
__device__ __forceinline__ bool mbar_test(uint32_t bar, uint32_t parity) {
    uint32_t ok;
    asm volatile(
        "{\n\t.reg .pred p;\n\t"
        "mbarrier.test_wait.parity.shared::cta.b64 p, [%1], %2;\n\t"
        "selp.u32 %0, 1, 0, p;\n\t}"
        : "=r"(ok) : "r"(bar), "r"(parity) : "memory");
    return __all_sync(0xffffffffu, ok);
}
__device__ __forceinline__ void mbar_expect(uint32_t bar, uint32_t bytes) {
    asm volatile("mbarrier.arrive.expect_tx.shared::cta.b64 _, [%0], %1;" ::"r"(bar), "r"(bytes) : "memory");
}
__device__ __forceinline__ void mbar_wait(uint32_t bar, uint32_t parity) {
    uint32_t ok, it = 0;
    do {
        asm volatile(
            "{\n\t.reg .pred p;\n\t"
            "mbarrier.try_wait.parity.shared::cta.b64 p, [%1], %2;\n\t"
            "selp.u32 %0, 1, 0, p;\n\t}"
            : "=r"(ok) : "r"(bar), "r"(parity) : "memory");
        if (++it > kSpinLimit) __trap();
    } while (!ok);
}
__device__ __forceinline__ bool mbar_try(uint32_t bar, uint32_t parity) {
    uint32_t ok;
    asm volatile(
        "{\n\t.reg .pred p;\n\t"
        "mbarrier.try_wait.parity.shared::cta.b64 p, [%1], %2;\n\t"
        "selp.u32 %0, 1, 0, p;\n\t}"
        : "=r"(ok) : "r"(bar), "r"(parity) : "memory");
    return __all_sync(0xffffffffu, ok);
}
__device__ __forceinline__ void mbar_wait_u(uint32_t bar, uint32_t parity) {
    for (uint32_t it = 0; !mbar_try(bar, parity); it++)
        if (it > kSpinLimit) __trap();
}
__device__ __forceinline__ void tma3d(uint32_t dst, const CUtensorMap* tm, int c0, int c1, int c2, uint32_t bar, uint64_t pol) {
    asm volatile(
        "cp.async.bulk.tensor.3d.shared::cluster.global.mbarrier::complete_tx::bytes.L2::cache_hint "
        "[%0], [%1, {%2, %3, %4}], [%5], %6;"
        ::"r"(dst), "l"(tm), "r"(c0), "r"(c1), "r"(c2), "r"(bar), "l"(pol) : "memory");
}
__device__ __forceinline__ void tma3d_prefetch(const CUtensorMap* tm, int c0, int c1, int c2, uint64_t pol) {
    asm volatile("cp.async.bulk.prefetch.tensor.3d.L2.global.L2::cache_hint [%0, {%1, %2, %3}], %4;"
                 ::"l"(tm), "r"(c0), "r"(c1), "r"(c2), "l"(pol) : "memory");
}
__device__ __forceinline__ uint64_t make_policy(bool keep) {
    uint64_t pol;
    if (keep) asm volatile("createpolicy.fractional.L2::evict_normal.b64 %0, 1.0;" : "=l"(pol));
    else      asm volatile("createpolicy.fractional.L2::evict_first.b64 %0, 1.0;" : "=l"(pol));
    return pol;
}
__device__ __forceinline__ void ldsm4(uint32_t (&r)[4], uint32_t addr) {
    asm volatile("ldmatrix.sync.aligned.m8n8.x4.shared.b16 {%0,%1,%2,%3}, [%4];"
                 : "=r"(r[0]), "=r"(r[1]), "=r"(r[2]), "=r"(r[3]) : "r"(addr) : "memory");
}
__device__ __forceinline__ void ldsm4t(uint32_t (&r)[4], uint32_t addr) {
    asm volatile("ldmatrix.sync.aligned.m8n8.x4.trans.shared.b16 {%0,%1,%2,%3}, [%4];"
                 : "=r"(r[0]), "=r"(r[1]), "=r"(r[2]), "=r"(r[3]) : "r"(addr) : "memory");
}
__device__ __forceinline__ void mma16816(float (&c)[4], const uint32_t (&a)[4], uint32_t b0, uint32_t b1) {
    asm volatile("mma.sync.aligned.m16n8k16.row.col.f32.bf16.bf16.f32 {%0,%1,%2,%3}, {%4,%5,%6,%7}, {%8,%9}, {%0,%1,%2,%3};"
                 : "+f"(c[0]), "+f"(c[1]), "+f"(c[2]), "+f"(c[3])
                 : "r"(a[0]), "r"(a[1]), "r"(a[2]), "r"(a[3]), "r"(b0), "r"(b1));
}
__device__ __forceinline__ float bf16r(float v) { return __bfloat162float(__float2bfloat16_rn(v)); }
__device__ __forceinline__ uint32_t pack_bf16(float lo, float hi) {
    uint32_t r;
    asm("cvt.rn.bf16x2.f32 %0, %1, %2;" : "=r"(r) : "f"(hi), "f"(lo));
    return r;
}
__device__ __forceinline__ bool elect() {
    uint32_t p;
    asm volatile("{\n\t.reg .pred e;\n\telect.sync _|e, 0xffffffff;\n\tselp.u32 %0, 1, 0, e;\n\t}" : "=r"(p));
    return p;
}
__device__ __forceinline__ float fast_sqrt(float v) {
    float r;
    asm("sqrt.approx.f32 %0, %1;" : "=f"(r) : "f"(v));
    return r;
}
__device__ __forceinline__ float ex2(float v) {
    float r;
    asm("ex2.approx.ftz.f32 %0, %1;" : "=f"(r) : "f"(v));
    return r;
}
__device__ __forceinline__ void st_packet(uint4* p, uint32_t a, uint32_t b, uint32_t c, uint32_t tag) {
    asm volatile(
        "{\n\t.reg .b64 lo, hi;\n\t.reg .b128 v;\n\t"
        "mov.b64 lo, {%1, %2};\n\tmov.b64 hi, {%3, %4};\n\tmov.b128 v, {lo, hi};\n\t"
        "st.relaxed.gpu.global.b128 [%0], v;\n\t}"
        ::"l"(p), "r"(a), "r"(b), "r"(c), "r"(tag) : "memory");
}
__device__ __forceinline__ void st_packet(uint4* p, float a, float b, float c, uint32_t tag) {
    st_packet(p, __float_as_uint(a), __float_as_uint(b), __float_as_uint(c), tag);
}
__device__ __forceinline__ uint4 ld_packet(const uint4* p) {
    uint4 v;
    asm volatile(
        "{\n\t.reg .b64 lo, hi;\n\t.reg .b128 v;\n\t"
        "ld.relaxed.gpu.global.b128 v, [%4];\n\t"
        "mov.b128 {lo, hi}, v;\n\tmov.b64 {%0, %1}, lo;\n\tmov.b64 {%2, %3}, hi;\n\t}"
        : "=r"(v.x), "=r"(v.y), "=r"(v.z), "=r"(v.w) : "l"(p) : "memory");
    return v;
}
__device__ __forceinline__ void red_packet(float4* p, float a, float b, float c) {
    asm volatile("red.relaxed.gpu.global.add.v4.f32 [%0], {%1, %2, %3, %4};"
                 ::"l"(p), "f"(a), "f"(b), "f"(c), "f"(1.f) : "memory");
}
#define POLL_UNTIL(pause, loads, done)            \
    for (uint32_t it_ = 0;; it_++) {              \
        loads;                                    \
        if (__all_sync(0xffffffffu, done)) break; \
        if (it_ > kSpinLimit) __trap();           \
        if (pause) __nanosleep(pause);            \
    }
__device__ __forceinline__ uint32_t round24(float v) {
    const uint32_t u = __float_as_uint(v);
    return u + ((u & 0x7f800000u) == 0x7f800000u ? 0u : 0x80u);
}
__device__ __forceinline__ void st_packet5(uint4* p, const float* v, uint32_t tag) {
    const uint32_t r0 = round24(v[0]), r1 = round24(v[1]), r2 = round24(v[2]), r3 = round24(v[3]), r4 = round24(v[4]);
    st_packet(p, __byte_perm(r0, r1, 0x5321), __byte_perm(r1, r2, 0x6532), __byte_perm(r2, r3, 0x7653),
              (r4 >> 8) | (tag << 24));
}
__device__ __forceinline__ void add_packet5(float (&a)[5], const uint4& v) {
    a[0] += __uint_as_float(v.x << 8);
    a[1] += __uint_as_float(__funnelshift_r(v.x, v.y, 16) & 0xffffff00u);
    a[2] += __uint_as_float(__funnelshift_r(v.y, v.z, 8) & 0xffffff00u);
    a[3] += __uint_as_float(v.z & 0xffffff00u);
    a[4] += __uint_as_float(v.w << 8);
}
__device__ __forceinline__ uint32_t now_ns() {
    uint32_t t;
    asm volatile("mov.u32 %0, %globaltimer_lo;" : "=r"(t));
    return t;
}
__device__ __forceinline__ int fresh_lane() {
    int lane = threadIdx.x & 31;
    asm volatile("" : "+r"(lane));
    return lane;
}
__device__ __forceinline__ void pause_ns(uint32_t ns) {
    const uint32_t t0 = now_ns();
    while (now_ns() - t0 < ns) __nanosleep(100);
}
__device__ __forceinline__ float bf_lo(uint32_t v) { return __uint_as_float(v << 16); }
__device__ __forceinline__ float bf_hi(uint32_t v) { return __uint_as_float(v & 0xffff0000u); }
__device__ __forceinline__ float warp_sum(float v) {
#pragma unroll
    for (int o = 16; o > 0; o >>= 1) v += __shfl_xor_sync(0xffffffffu, v, o);
    return v;
}

constexpr float kScale = 0.07216878364870322f * 1.4426950408889634f;

struct Attn {
    float m, l;
    float acc[3][4];
};

__device__ __forceinline__ uint32_t probability(Attn& st, float s) {
    const float e = ex2(s - st.m);
    st.l += e;
    const float hi = bf16r(e);
    const uint32_t hl = pack_bf16(hi, e - hi);
    uint32_t pv;
    asm volatile("movmatrix.sync.aligned.m8n8.trans.b16 %0, %1;" : "=r"(pv) : "r"(hl));
    return pv;
}

__device__ __forceinline__ uint32_t softmax_step(Attn& st, float s) {
    if (__any_sync(0xffffffffu, s > st.m)) {
        float mx = fmaxf(s, __shfl_xor_sync(0xffffffffu, s, 4));
        mx = fmaxf(mx, __shfl_xor_sync(0xffffffffu, mx, 8));
        mx = fmaxf(mx, __shfl_xor_sync(0xffffffffu, mx, 16));
        mx = fmaxf(mx, st.m);
        const float corr = ex2(st.m - mx);
        st.m = mx;
        st.l *= corr;
#pragma unroll
        for (int a = 0; a < 3; a++)
#pragma unroll
            for (int i = 0; i < 4; i++) st.acc[a][i] *= corr;
    }
    return probability(st, s);
}

__global__ void __launch_bounds__(kThreads, 1)
fused_decode_kernel(const __grid_constant__ Params P) {
    extern __shared__ __align__(1024) unsigned char smem[];
    const uint32_t sbase = (uint32_t)__cvta_generic_to_shared(smem);
    const uint32_t sync0 = sbase + kOffSync;
    float* const wbuf = reinterpret_cast<float*>(smem + kOffWbuf);

    const int lane = threadIdx.x & 31;
    const int w = __shfl_sync(0xffffffffu, threadIdx.x >> 5, 0);
    const int cta = blockIdx.x;
    const int h = cta >> 2, jq = cta & 3;

    if (w >= 10) {
        const int i0 = 80 * (w - 10) + lane;
#pragma unroll
        for (int i = 0; i < 3; i++)
            if (i < 2 || lane < 16)
                asm volatile("cp.async.cg.shared.global [%0], [%1], 16;"
                             ::"r"(sbase + kOffWbuf + 16 * (i0 + 32 * i)), "l"(reinterpret_cast<const uint4*>(P.x) + i0 + 32 * i) : "memory");
    }
    if (elect()) {
        if (w == 8) {
#pragma unroll
            for (int i = 0; i < kSlots; i++) {
                mbar_init(sbase + kOffFull + 8 * i, 1);
                mbar_init(sbase + kOffEmpty + 8 * i, 8);
            }
        } else if (w == 9) {
#pragma unroll
            for (int i = 0; i < 10; i++) asm volatile("prefetch.tensormap [%0];" ::"l"(&P.tm[i]) : "memory");
        } else if (w == 10) {
#pragma unroll
            for (int i = 0; i < 14; i++) mbar_init(sync0 + 8 * i, (8 * i == kBarRows || 8 * i >= kBarSentY) ? 8 : 1);
        }
        if (w != 9) asm volatile("fence.mbarrier_init.release.cluster;" ::: "memory");
    }
    __syncwarp();
    if (w == 8) {
        asm volatile("bar.arrive 1, %0;" ::"n"(kThreads) : "memory");
    } else {
        asm volatile("bar.sync 1, %0;" ::"n"(kThreads) : "memory");
    }

    if (w < 8) {
        asm volatile("setmaxnreg.inc.sync.aligned.u32 232;");
        const uint32_t full0 = sbase + kOffFull;
        const uint32_t frag0 = sbase + w * 1024 + (lane & 7) * 128 + (((lane >> 3) ^ (lane & 7)) << 4), frag1 = frag0 ^ 64;
        auto frag_addr = [&](uint32_t s, int k) { return ((k & 1) ? frag1 : frag0) + s * (8 * kSlotBytes) + (k >> 1) * 8192; };
        uint32_t par = 0, rpos = 0, nrows = 0;
        auto wait_tile = [&](uint32_t s) { mbar_wait(full0 + 8 * s, (par >> s) & 1u); };
        auto tile_ready = [&](uint32_t s) { return mbar_test(full0 + 8 * s, (par >> s) & 1u); };
        auto release = [&](uint32_t s) {
            par ^= 1u << s;
            __syncwarp();
            if (elect()) mbar_arrive(full0 + 8 * s + (kOffEmpty - kOffFull));
        };
        auto ring_release = [&]() {
            release(rpos);
            if (++rpos == kRing) rpos = 0;
        };
        auto row_acquire = [&]() { mbar_wait(sync0 + kBarFree, (nrows & 1) ^ 1); };
        auto row_publish = [&]() {
            __syncwarp();
            if (elect()) mbar_arrive(sync0 + kBarRows);
            nrows++;
        };

        uint32_t rf[8][6][4];
#pragma unroll
        for (int i = 0; i < 8; i++)
#pragma unroll
            for (int s = 0; s < 6; s++)
#pragma unroll
                for (int k = 0; k < 4; k++) rf[i][s][k] = 0;

#pragma unroll 1
        for (int pc = 0;; pc++) {
            const uint32_t op = P.prog[pc];
            const uint32_t kind = op & 7u;
            if (kind == OP_END) break;
            const int lane = fresh_lane();
            const int g = lane >> 2, t = lane & 3;
            float* const row = wbuf + w * kWRow;

            if (kind == OP_SEG) {
                const uint32_t b = (op >> 3) & 1u;
                mbar_wait(sync0 + kBarQ + 8 * b, (op >> 4) & 1u);
                const uint2* qf = reinterpret_cast<const uint2*>(smem + kOffQf) + b * 48 + (lane & 7);
                Attn st;
                st.m = -INFINITY; st.l = 0.f;
#pragma unroll
                for (int a = 0; a < 3; a++)
#pragma unroll
                    for (int i = 0; i < 4; i++) st.acc[a][i] = 0.f;

                if (op & (1u << 7)) {
                    float c[4][4] = {};
#pragma unroll
                    for (int k = 0; k < 6; k++) {
                        const uint2 q = qf[8 * k];
#pragma unroll
                        for (int i = 0; i < 4; i++) mma16816(c[i], rf[2 * i][k], q.x, q.y);
                    }
                    float sc[4];
#pragma unroll
                    for (int i = 0; i < 4; i++) sc[i] = (c[i][0] + c[i][3]) * kScale;
                    float mx = fmaxf(fmaxf(sc[0], sc[1]), fmaxf(sc[2], sc[3]));
                    mx = fmaxf(mx, __shfl_xor_sync(0xffffffffu, mx, 4));
                    mx = fmaxf(mx, __shfl_xor_sync(0xffffffffu, mx, 8));
                    st.m = fmaxf(mx, __shfl_xor_sync(0xffffffffu, mx, 16));
                    uint32_t pv[4];
#pragma unroll
                    for (int i = 0; i < 4; i++) pv[i] = probability(st, sc[i]);
#pragma unroll
                    for (int i = 0; i < 4; i++)
#pragma unroll
                        for (int k = 0; k < 6; k++)
                            mma16816(st.acc[k >> 1], rf[2 * i + 1][k], (g >> 1) == 2 * (k & 1) ? pv[i] : 0u,
                                     (g >> 1) == 2 * (k & 1) + 1 ? pv[i] : 0u);
                }

                uint32_t lo = P.prog[pc + 1], hi = P.prog[pc + 2];
                pc += 2;
                bool haveK = false;
#pragma unroll 1
                while (lo & 15u) {
                    const bool rel = lo & 4u;
                    uint32_t sK = kRing - 2 + 2 * (lo & 3u), sV = sK + 1;
                    if (!(lo & 3u)) {
                        sK = rpos;
                        sV = rpos == kRing - 1 ? 0 : rpos + 1;
                        rpos = sV == kRing - 1 ? 0 : sV + 1;
                    }
                    lo = __funnelshift_r(lo, hi, 4);
                    hi >>= 4;
                    if (!haveK) wait_tile(sK);
                    const bool haveV = tile_ready(sV);
                    float c[2][4] = {};
#pragma unroll
                    for (int k = 0; k < 6; k++) {
                        uint32_t a[4];
                        ldsm4(a, frag_addr(sK, k));
                        const uint2 q = qf[8 * k];
                        mma16816(c[k & 1], a, q.x, q.y);
                    }
                    if (rel) release(sK);
                    const uint32_t pv = softmax_step(st, ((c[0][0] + c[0][3]) + (c[1][0] + c[1][3])) * kScale);
                    if (!haveV) wait_tile(sV);
                    haveK = tile_ready((lo & 3u) ? kRing - 2 + 2 * (lo & 3u) : rpos);
#pragma unroll
                    for (int k = 0; k < 6; k++) {
                        uint32_t a[4];
                        ldsm4t(a, frag_addr(sV, k));
                        mma16816(st.acc[k >> 1], a, (g >> 1) == 2 * (k & 1) ? pv : 0u, (g >> 1) == 2 * (k & 1) + 1 ? pv : 0u);
                    }
                    if (rel) release(sV);
                }

                float l = st.l;
                l += __shfl_xor_sync(0xffffffffu, l, 4);
                l += __shfl_xor_sync(0xffffffffu, l, 8);
                l += __shfl_xor_sync(0xffffffffu, l, 16);
                row_acquire();
#pragma unroll
                for (int a = 0; a < 3; a++) {
                    row[64 * a + 16 * t + g] = st.acc[a][0] + st.acc[a][1];
                    row[64 * a + 16 * t + g + 8] = st.acc[a][2] + st.acc[a][3];
                }
                if (lane == 0) { wbuf[8 * kWRow + w] = st.m; wbuf[8 * kWRow + 8 + w] = l; }
                row_publish();
            } else if (kind == OP_RFLOAD) {
#pragma unroll 1
                for (uint32_t tile = (op >> 3) & 7u; tile < (op >> 6); tile++) {
                    wait_tile(rpos);
#pragma unroll
                    for (int i = 0; i < 8; i++) {
                        if (tile == i) {
#pragma unroll
                            for (int k = 0; k < 6; k++) {
                                if (i & 1) ldsm4t(rf[i][k], frag_addr(rpos, k));
                                else ldsm4(rf[i][k], frag_addr(rpos, k));
                            }
                        }
                    }
                    ring_release();
                }
            } else if (kind == OP_QPROJ) {
                const uint32_t mask = (op >> 3) & 3u;
#pragma unroll 1
                for (uint32_t b = 0; b < 2; b++)
                    if ((mask >> b) & 1u) mbar_wait(sync0 + kBarXn + 8 * b, (op >> 5) & 1u);
                const uint32_t bb = mask == 3u ? (g & 1) : (mask >> 1);
                const uint32_t* xs = reinterpret_cast<const uint32_t*>(smem + kOffXn) + bb * 80 + 4 * w + t;
                float acc[3][4] = {};
#pragma unroll 1
                for (int p = 0; p < 3; p++) {
                    wait_tile(rpos);
                    if (p < 2 || w < 4) {
                        const uint32_t xv = xs[32 * p];
                        const uint32_t shrink = p == 2 ? 4096 : 0;
#pragma unroll
                        for (int k = 0; k < 6; k++) {
                            uint32_t a[4];
                            ldsm4t(a, frag_addr(rpos, k) - (k >> 1) * shrink);
                            mma16816(acc[k >> 1], a, (g >> 1) == 2 * (k & 1) ? xv : 0u, (g >> 1) == 2 * (k & 1) + 1 ? xv : 0u);
                        }
                    }
                    ring_release();
                }
#pragma unroll 1
                for (uint32_t b = 0; b < 2; b++) {
                    if (!((mask >> b) & 1u)) continue;
                    row_acquire();
#pragma unroll
                    for (int a = 0; a < 3; a++) {
                        row[64 * a + 16 * t + g] = b ? acc[a][1] : acc[a][0];
                        row[64 * a + 16 * t + g + 8] = b ? acc[a][3] : acc[a][2];
                    }
                    row_publish();
                }
            } else {
                const uint32_t mask = (op >> 3) & 3u;
                const uint32_t bb = mask == 3u ? (g & 1) : (mask >> 1);
                const uint32_t* ob = reinterpret_cast<const uint32_t*>(smem + kOffObf) + bb * 24 + t;
                const uint32_t roff = ((lane & 7) + 8 * (lane >> 4)) * 128 + ((((lane >> 3) & 1) ^ (lane & 7)) << 4);
                uint32_t sl[3];
#pragma unroll
                for (int p = 0; p < 3; p++) {
                    sl[p] = rpos;
                    if (++rpos == kRing) rpos = 0;
                }
                auto frag = [&](uint32_t (&a)[4], int p, int mt) {
                    ldsm4t(a, ((sbase + sl[p] * 8 * kSlotBytes + roff) ^ (((5 * w + mt) & 3) << 5)) + ((5 * w + mt) >> 2) * 2048);
                };
                uint32_t a0[5][4];
                wait_tile(sl[0]);
#pragma unroll
                for (int mt = 0; mt < 5; mt++) frag(a0[mt], 0, mt);
                release(sl[0]);
                wait_tile(sl[1]);
                wait_tile(sl[2]);
                row_acquire();
                if (mask & 1u) mbar_wait(sync0 + kBarO, (op >> 5) & 1u);
                if (mask & 2u) mbar_wait(sync0 + kBarO + 8, (op >> 5) & 1u);
                float c[3][4] = {};
#pragma unroll
                for (int p = 0; p < 3; p++) {
                    const uint32_t b0 = ob[8 * p], b1 = ob[8 * p + 4];
#pragma unroll
                    for (int mt = 0; mt < 5; mt++) {
                        if (p > 0) frag(a0[mt], p, mt);
                        const bool on = (g >> 1) == (mt & 3);
                        mma16816(c[mt == 4 ? 2 : (mt & 1)], a0[mt], on ? b0 : 0u, on ? b1 : 0u);
                    }
                    if (p > 0) release(sl[p]);
                }
                row[16 * t + g] = c[0][0] + c[1][0]; row[80 + 16 * t + g] = c[0][1] + c[1][1];
                row[16 * t + g + 8] = c[0][2] + c[1][2]; row[80 + 16 * t + g + 8] = c[0][3] + c[1][3];
                if (t == 0) {
                    row[64 + g] = c[2][0]; row[144 + g] = c[2][1];
                    row[72 + g] = c[2][2]; row[152 + g] = c[2][3];
                }
                __syncwarp();
                if (lane < 27) {
                    const bool last = ((op >> 5) & 3u) == 3u;
                    float4* dst = (last ? g_out[0][cta % kOutReplicas] : g_acc[0][(op >> 5) & 3u]) + (27 * w + lane) * kAccPad;
                    const float* y = row + 3 * lane;
                    if (mask & 1u) red_packet(dst, y[0], y[1], lane < 26 ? y[2] : 0.f);
                    if (mask & 2u) red_packet(dst + (last ? kOutReplicas : 3) * kAccPad * kAccPackets, y[80], y[81], lane < 26 ? y[82] : 0.f);
                }
                __syncwarp();
                if (lane < 2 && ((mask >> lane) & 1u)) mbar_arrive(sync0 + kBarSentY + 8 * lane);
            }
        }
    } else {
        asm volatile("setmaxnreg.dec.sync.aligned.u32 40;");
        if (w == 8) {
            if (elect()) {
#pragma unroll
                for (int p = 0; p < kRing; p++) {
                    const CUtensorMap* tm = &P.tm[p == 2 ? 8 : 4];
                    mbar_expect(sbase + kOffFull + 8 * p, p == 2 ? 4 * kSlotBytes : 8 * kSlotBytes);
                    tma3d(sbase + p * 8 * kSlotBytes, tm, 0, 160 * jq + 64 * p, 3 * h, sbase + kOffFull + 8 * p, make_policy(false));
                    tma3d_prefetch(tm, 0, 160 * jq + 64 * p, 3 * h, make_policy(true));
                }
            }
            __syncwarp();
            const int rowA = h * 4096 + 3072 + 256 * jq, rowB = h * 4096 + 1024 * jq;
            const int rowWq = 160 * jq, rowWo = 192 * h + 48 * jq;
            uint32_t credit = kCredit, na = 0;
            const uint64_t polKeep = make_policy(true), polStream = make_policy(false);
            uint32_t fifo = 0x012u, queued = 7u, stale = 0, par = 7u, nfl = kRing, next = now_ns() + kStartDelay;
            const uint32_t rot = 64u * 11u * ((h & 3) + ((h >> 2) & 3) + (h >> 4));
            auto coord = [&](uint32_t e) {
                const uint32_t off = (e >> 10) & 0x3ffffu;
                if ((e & 6u) == 2u) return (int)((off & ~0x3ffu) + ((off + rot) & 0x3c0u)) + rowB;
                return (int)off + ((e & 4u) ? ((e & 2u) ? rowWo : rowWq) : rowA);
            };
            auto interval = [&](uint32_t e) {
                return (e & 6u) == 6u ? kTauWo : ((e & LD_HANDOFF) ? kTauHandoff : kTau) >> ((e >> 28) & 1u);
            };
            auto map = [&](uint32_t e) { return &P.tm[(e & 7u) + ((e >> 26) & 4u)]; };
            uint32_t latest = 2;
            auto slot_free = [&](uint32_t s) { return mbar_test(sbase + kOffEmpty + 8 * s, ((par >> s) & 1u) ^ 1u); };
            auto landed = [&](uint32_t s) { return mbar_test(sbase + kOffFull + 8 * s, ((par >> s) & 1u) ^ 1u); };
            auto load = [&](uint32_t e, bool counted) {
                const uint32_t s = (e >> 4) & 15u;
                const int c1 = coord(e), c2 = ((e >> 1) & 3u) == 2u ? 3 * h : 0;
                if (elect()) {
                    mbar_expect(sbase + kOffFull + 8 * s, (e & 6u) == 6u ? 20480 : (8 * kSlotBytes) >> ((e >> 28) & 1u));
                    tma3d(sbase + s * 8 * kSlotBytes, map(e), 0, c1, c2, sbase + kOffFull + 8 * s, polStream);
                    if (e & LD_KEEP) tma3d_prefetch(map(e), 0, c1, c2, polKeep);
                }
                if (counted) {
                    fifo = (fifo << 4) | s;
                    queued |= 1u << s;
                    nfl++;
                    latest = s;
                }
                par ^= 1u << s;
            };
            uint32_t m = 0, pfd = 0;
#pragma unroll 1
            for (uint32_t n = kRing;; n++) {
                const uint32_t e = P.loads[n];
                if (!(e & LD_VALID)) break;
                const uint32_t s = (e >> 4) & 15u;
                if (m < n) m = n;
                const uint32_t look = (e & LD_FAR) ? kLookFar : kLook;
                for (uint32_t it = 0; !slot_free(s); it++) {
                    if (it > 16 * kSpinLimit) __trap();
                    const uint32_t f = P.loads[m];
                    if (m >= n + look || !(f & LD_VALID)) continue;
                    if (f & LD_HIT) { m++; continue; }
                    const uint32_t now = now_ns();
                    if ((int)(now - next) >= 0 && landed(latest)) {
                        if (elect()) tma3d_prefetch(map(f), 0, coord(f), ((f >> 1) & 3u) == 2u ? 3 * h : 0, polStream);
                        next = now + interval(f);
                        pfd |= 1u << (m & 31u);
                        m++;
                    }
                }
                stale |= queued & (1u << s);
                queued &= ~(1u << s);
                if (e & LD_ANCHOR) {
                    const uint32_t t0 = __shfl_sync(0xffffffffu, *reinterpret_cast<volatile uint32_t*>(smem + kOffAnchor), 0) + P.anchorDelay[na];
                    if (m <= n || (int)(t0 - next) > 0) next = t0;
                    credit = P.anchorCredit[na++];
                }
                const bool counted = !(e & LD_HIT) && !((pfd >> (n & 31u)) & 1u);
                pfd &= ~(1u << (n & 31u));
                if (counted) {
                    for (const uint32_t win = n < kStartLoads ? kStartWindow : kWindow; nfl >= win; nfl--) {
                        const uint32_t o = (fifo >> (4 * nfl - 4)) & 15u;
                        if ((stale >> o) & 1u) {
                            stale ^= 1u << o;
                        } else {
                            mbar_wait_u(sbase + kOffFull + 8 * o, ((par >> o) & 1u) ^ 1u);
                            queued ^= 1u << o;
                        }
                    }
                    uint32_t now = now_ns();
                    while ((int)(now - next) < 0) now = now_ns();
                    if ((int)(now - credit - next) > 0) next = now - credit;
                    next += interval(e);
                }
                load(e, counted);
            }
        } else {
            if (w == 9) {
#pragma unroll 1
                for (int n = 0;; n++) {
                    const uint32_t job = P.merge[n];
                    if ((job & 3u) == MG_END) break;
                    const uint32_t b = (job >> 2) & 1u;
                    const uint32_t tag = 1 + ((job >> 3) & 3u);
                    mbar_wait(sync0 + kBarRows, n & 1);
                    if ((job & 3u) == MG_Q) {
                        float o[5] = {}, e[5] = {};
                        const float* ext = wbuf + 2 * (lane & 3) * kWRow + 5 * min(32 + (lane >> 2), 38);
#pragma unroll
                        for (int k = 0; k < 5; k++) e[k] = ext[k] + ext[kWRow + k];
#pragma unroll
                        for (int i = 0; i < 8; i++)
#pragma unroll
                            for (int k = 0; k < 5; k++) o[k] += wbuf[i * kWRow + 5 * lane + k];
                        st_packet5(&g_q[b][h][jq][lane], o, tag);
#pragma unroll
                        for (int k = 0; k < 5; k++) {
                            e[k] += __shfl_xor_sync(0xffffffffu, e[k], 1);
                            e[k] += __shfl_xor_sync(0xffffffffu, e[k], 2);
                        }
                        if ((lane & 3) == 0) st_packet5(&g_q[b][h][jq][32 + (lane >> 2)], e, tag);
                        __syncwarp();
                        if (lane == 0) mbar_arrive(sync0 + kBarSentQ + 8 * b);
                    } else {
                        float2* cp = reinterpret_cast<float2*>(smem + kOffCpart) + b * (kWRow / 2) + 3 * lane;
                        float2* cml = reinterpret_cast<float2*>(smem + kOffMl + 64) + b;
                        const float4* ml = reinterpret_cast<const float4*>(smem + kOffMl);
                        const bool merge = !(job & 32u);
                        const float2 pml = merge ? *cml : make_float2(-INFINITY, 0.f);
                        const float4 m0 = ml[0], m1 = ml[1];
                        float sc[8] = {m0.x, m0.y, m0.z, m0.w, m1.x, m1.y, m1.z, m1.w};
                        const float M = fmaxf(fmaxf(fmaxf(fmaxf(sc[0], sc[1]), fmaxf(sc[2], sc[3])),
                                                    fmaxf(fmaxf(sc[4], sc[5]), fmaxf(sc[6], sc[7]))), pml.x);
#pragma unroll
                        for (int i = 0; i < 8; i++) sc[i] = ex2(sc[i] - M);
                        const float ps = ex2(pml.x - M);
                        float2 o[3];
#pragma unroll
                        for (int k = 0; k < 3; k++) {
                            o[k] = merge ? cp[k] : make_float2(0.f, 0.f);
                            o[k].x *= ps; o[k].y *= ps;
                        }
#pragma unroll
                        for (int i = 0; i < 8; i++)
#pragma unroll
                            for (int k = 0; k < 3; k++) {
                                const float2 v = reinterpret_cast<const float2*>(wbuf)[i * (kWRow / 2) + 3 * lane + k];
                                o[k].x = fmaf(v.x, sc[i], o[k].x);
                                o[k].y = fmaf(v.y, sc[i], o[k].y);
                            }
                        const float4 l0 = ml[2], l1 = ml[3];
                        const float L = fmaf(pml.y, ps, ((l0.x * sc[0] + l0.y * sc[1]) + (l0.z * sc[2] + l0.w * sc[3])) +
                                                        ((l1.x * sc[4] + l1.y * sc[5]) + (l1.z * sc[6] + l1.w * sc[7])));
                        if (job & 64u) {
                            uint4* dst = &g_p[b][h][lane >> 3][jq][2 * (lane & 7)];
                            st_packet(dst, o[0].x, o[0].y, o[1].x, tag);
                            st_packet(dst + 1, o[1].y, o[2].x, o[2].y, tag);
                            if (lane < 8) st_packet(&g_p[b][h][lane >> 1][jq][16 + (lane & 1)], M, L, 0.f, tag);
                            if (lane == 0) mbar_arrive(sync0 + kBarSentP + 8 * b);
                        } else {
#pragma unroll
                            for (int k = 0; k < 3; k++) cp[k] = o[k];
                            __syncwarp();
                            if (lane == 0) *cml = make_float2(M, L);
                        }
                    }
                    __syncwarp();
                    if (lane == 0) mbar_arrive(sync0 + kBarFree);
                }
            } else {
                const uint32_t b = w - 10;
                __nv_bfloat16* const xn = reinterpret_cast<__nv_bfloat16*>(smem + kOffXn) + b * 160;
                __nv_bfloat16* const qd = reinterpret_cast<__nv_bfloat16*>(smem + kOffQf) + b * 192;
                __nv_bfloat16* const ob = reinterpret_cast<__nv_bfloat16*>(smem + kOffObf) + b * 48;
                uint2* const own = reinterpret_cast<uint2*>(smem + kOffOwn) + 2 * b;
#pragma unroll 1
                for (uint32_t layer = 0; layer < 4; layer++) {
                    const uint32_t tag = layer + 1;
                    {
                        int lane = fresh_lane();
                        uint32_t x01[7], x2[7];
                        if (layer == 0) {
                            const uint4* stage = reinterpret_cast<const uint4*>(wbuf) + 80 * b;
                            asm volatile("cp.async.wait_all;" ::: "memory");
                            __syncwarp();
#pragma unroll
                            for (int i = 0; i < 7; i++) {
                                const int p = lane + 32 * i, u = p % 27;
                                const unsigned short* xp = reinterpret_cast<const unsigned short*>(stage) + (p / 27) * 80 + 3 * u;
                                x01[i] = p < kAccPackets ? xp[0] | ((uint32_t)xp[1] << 16) : 0u;
                                x2[i] = (p < kAccPackets && u < 26) ? xp[2] : 0u;
                            }
                        } else {
                            mbar_wait(sync0 + kBarSentY + 8 * b, (layer - 1) & 1);
                            pause_ns(kDelayX);
                            uint4 v[7];
                            const uint4* src = reinterpret_cast<const uint4*>(&g_acc[b][layer - 1][lane * kAccPad]);
                            const uint32_t done = __float_as_uint(kAccDone);
                            POLL_UNTIL(kPauseX, v[0] = ld_packet(src + (27 * (cta & 7) + min(lane, 26) - lane) * kAccPad), v[0].w == done);
                            POLL_UNTIL(kPauseX,
                                v[0] = ld_packet(src); v[1] = ld_packet(src + 32 * kAccPad); v[2] = ld_packet(src + 64 * kAccPad);
                                v[3] = ld_packet(src + 96 * kAccPad); v[4] = ld_packet(src + 128 * kAccPad);
                                v[5] = ld_packet(src + 160 * kAccPad); v[6] = ld_packet(src + (lane < 24 ? 192 * kAccPad : 0)),
                                v[0].w == done && v[1].w == done && v[2].w == done && v[3].w == done && v[4].w == done &&
                                    v[5].w == done && v[6].w == done);
#pragma unroll
                            for (int i = 0; i < 7; i++) {
                                x01[i] = pack_bf16(__uint_as_float(v[i].x), __uint_as_float(v[i].y));
                                x2[i] = pack_bf16(__uint_as_float(v[i].z), 0.f);
                            }
                            if (lane >= 24) x01[6] = x2[6] = 0u;
                        }
#pragma unroll
                        for (int i = 0; i < 7; i++) {
                            const int p = lane + 32 * i;
                            if ((p & 127) == cta && p < kAccPackets) {
                                own[i >> 2] = make_uint2(x01[i], x2[i]);
                            }
                        }
                        float sum = 0.f;
#pragma unroll
                        for (int i = 0; i < 7; i++) sum += (bf_lo(x01[i]) + bf_hi(x01[i])) + bf_lo(x2[i]);
                        const float mean = warp_sum(sum) * (1.f / 640.f);
                        float sq = 0.f;
#pragma unroll
                        for (int i = 0; i < 7; i++) {
                            const bool none = i == 6 && lane >= 24;
                            const float d0 = none ? 0.f : bf_lo(x01[i]) - mean, d1 = none ? 0.f : bf_hi(x01[i]) - mean;
                            const bool last = lane == 26 - 5 * i || lane == 53 - 5 * i;
                            const float d2 = (none || last) ? 0.f : bf_lo(x2[i]) - mean;
                            sq += fmaf(d0, d0, fmaf(d1, d1, d2 * d2));
                        }
                        const float var = warp_sum(sq) * (1.f / 640.f);
                        const float meanb = bf16r(mean);
                        const float rden = __fdividef(1.f, bf16r(fast_sqrt(bf16r(bf16r(var) + 1e-5f))));
#pragma unroll
                        for (int i = 0; i < 7; i++) {
                            const uint32_t q = lane + 32 * i - 54 * jq;
                            if (q < 54u) {
                                const int c = 3 * q - (q >= 27u);
                                xn[c] = __float2bfloat16_rn(bf16r(bf_lo(x01[i]) - meanb) * rden);
                                xn[c + 1] = __float2bfloat16_rn(bf16r(bf_hi(x01[i]) - meanb) * rden);
                                if (q != 26u && q != 53u) xn[c + 2] = __float2bfloat16_rn(bf16r(bf_lo(x2[i]) - meanb) * rden);
                            }
                        }
                        if (lane == 0) *reinterpret_cast<volatile uint32_t*>(smem + kOffAnchor) = now_ns();
                        __syncwarp();
                        if (lane == 0) mbar_arrive(sync0 + kBarXn + 8 * b);
                        if (layer >= 2 && lane < 4 && cta + 128 * (lane >> 1) < kAccPackets)
                            g_acc[b][layer - 2][(cta + 128 * (lane >> 1)) * kAccPad + (lane & 1)] = make_float4(0.f, 0.f, 0.f, 0.f);
                        __syncwarp();
                    }
                    {
                        const int lane = fresh_lane();
                        mbar_wait(sync0 + kBarSentQ + 8 * b, layer & 1);
                        if (layer == 0 || (layer == 1 && b == 1)) pause_ns(kDelayIdle);
                        uint4 v[5];
                        const uint4* src = &g_q[b][h][0][lane];
                        const uint4* ext = &g_q[b][h][lane & 3][lane < 28 ? 32 + (lane >> 2) : 38];
                        POLL_UNTIL(0,
                            v[0] = ld_packet(src); v[1] = ld_packet(src + 40); v[2] = ld_packet(src + 80);
                            v[3] = ld_packet(src + 120); v[4] = ld_packet(ext),
                            (v[0].w >> 24) == tag && (v[1].w >> 24) == tag && (v[2].w >> 24) == tag &&
                                (v[3].w >> 24) == tag && (v[4].w >> 24) == tag);
                        __syncwarp();
                        auto store_q = [&](int d, float q) {
                            qd[(d & ~31) + ((d >> 3) & 1) * 16 + ((d >> 1) & 3) * 4 + ((d >> 4) & 1) * 2 + (d & 1)] =
                                __float2bfloat16_rn(q);
                        };
                        float a[5] = {};
#pragma unroll
                        for (int i = 0; i < 4; i++) add_packet5(a, v[i]);
#pragma unroll
                        for (int k = 0; k < 5; k++) store_q(5 * lane + k, a[k]);
                        float e[5] = {};
                        add_packet5(e, v[4]);
#pragma unroll
                        for (int k = 0; k < 5; k++) {
                            e[k] += __shfl_xor_sync(0xffffffffu, e[k], 1);
                            e[k] += __shfl_xor_sync(0xffffffffu, e[k], 2);
                            const int d = 160 + 5 * (lane >> 2) + k;
                            if ((lane & 3) == 0 && d < 192) store_q(d, e[k]);
                        }
                        __syncwarp();
                        if (lane == 0) mbar_arrive(sync0 + kBarQ + 8 * b);
                    }
                    {
                        const int lane = fresh_lane();
                        mbar_wait(sync0 + kBarSentP + 8 * b, layer & 1);
                        pause_ns((b == 0 && (layer == 0 || layer == 3)) ? kDelayIdle : (layer == 3 ? 0 : kDelayP));
                        uint4 v0, v1, ml;
                        const uint4* src = &g_p[b][h][jq][2 * (lane >> 4)][lane & 15];
                        const uint4* mls = &g_p[b][h][jq][lane & 3][16];
                        POLL_UNTIL(0, v0 = ld_packet(src); v1 = ld_packet(src + 18); ml = ld_packet(mls),
                                   v0.w == tag && v1.w == tag && ml.w == tag);
                        __syncwarp();
                        const float mi = __uint_as_float(ml.x);
                        float M = fmaxf(mi, __shfl_xor_sync(0xffffffffu, mi, 1));
                        M = fmaxf(M, __shfl_xor_sync(0xffffffffu, M, 2));
                        const float sc = ex2(mi - M);
                        float L = __uint_as_float(ml.y) * sc;
                        L += __shfl_xor_sync(0xffffffffu, L, 1);
                        L += __shfl_xor_sync(0xffffffffu, L, 2);
                        const float s0 = __shfl_sync(0xffffffffu, sc, 2 * (lane >> 4));
                        const float s1 = __shfl_sync(0xffffffffu, sc, 2 * (lane >> 4) + 1);
                        float o0 = fmaf(__uint_as_float(v0.x), s0, __uint_as_float(v1.x) * s1);
                        float o1 = fmaf(__uint_as_float(v0.y), s0, __uint_as_float(v1.y) * s1);
                        float o2 = fmaf(__uint_as_float(v0.z), s0, __uint_as_float(v1.z) * s1);
                        o0 += __shfl_xor_sync(0xffffffffu, o0, 16);
                        o1 += __shfl_xor_sync(0xffffffffu, o1, 16);
                        o2 += __shfl_xor_sync(0xffffffffu, o2, 16);
                        if (lane < 16) {
                            ob[3 * lane] = __float2bfloat16_rn(__fdividef(o0, L));
                            ob[3 * lane + 1] = __float2bfloat16_rn(__fdividef(o1, L));
                            ob[3 * lane + 2] = __float2bfloat16_rn(__fdividef(o2, L));
                        }
                        __syncwarp();
                        if (lane == 0) mbar_arrive(sync0 + kBarO + 8 * b);
                        const int p = cta + 128 * lane;
                        if (p < kAccPackets) {
                            const uint2 v = own[lane];
                            red_packet((layer == 3 ? g_out[b][0] : g_acc[b][layer]) + p * kAccPad, bf_lo(v.x), bf_hi(v.x), bf_lo(v.y));
                        }
                    }
                }
                {
                    mbar_wait(sync0 + kBarSentY + 8 * b, 1);
                    const int p = cta + 128 * ((lane / kOutReplicas) & 1), r = lane % kOutReplicas;
                    float4* src = &g_out[b][r][(p < kAccPackets ? p : cta) * kAccPad];
                    const float want = kCtas / kOutReplicas + (r == 0);
                    uint4 v;
                    for (uint32_t it = 0;; it++) {
                        v = ld_packet(reinterpret_cast<const uint4*>(src));
                        if (__all_sync(0xffffffffu, v.w == __float_as_uint(want))) break;
                        if (it > kSpinLimit) __trap();
                    }
                    float o0 = __uint_as_float(v.x), o1 = __uint_as_float(v.y), o2 = __uint_as_float(v.z);
#pragma unroll
                    for (int o = 1; o < kOutReplicas; o <<= 1) {
                        o0 += __shfl_xor_sync(0xffffffffu, o0, o);
                        o1 += __shfl_xor_sync(0xffffffffu, o1, o);
                        o2 += __shfl_xor_sync(0xffffffffu, o2, o);
                    }
                    if (lane < 2 * kOutReplicas && p < kAccPackets) {
                        if (r < 3 - (p % 27 == 26))
                            P.out[b * 640 + (p / 27) * 80 + 3 * (p % 27) + r] = __float2bfloat16_rn(r == 0 ? o0 : r == 1 ? o1 : o2);
                        *src = make_float4(0.f, 0.f, 0.f, 0.f);
                        if (r == 0) g_acc[b][2][p * kAccPad] = make_float4(0.f, 0.f, 0.f, 0.f);
                    }
                }
            }
        }
    }
}


struct Sched {
    Params& P;
    int np = 0, nm = 0, nl = 0, rslot = 0, mark = 0;
    uint32_t pending = 0;
    enum { RF = 1 << 7, FIRST = 1 << 11, PUB = 1 << 12 };

    void handoff_begin() { mark = nl; }
    void handoff_end() { for (int i = mark; i < nl; i++) P.loads[i] |= LD_HANDOFF; }
    void slot(uint32_t e, int s) { P.loads[nl++] = e | (s << 4); }
    void ring(uint32_t e) {
        slot(e | pending, rslot);
        pending = 0;
        rslot = (rslot + 1) % kRing;
    }
    static uint32_t tile(int isB, int b, int idx, int v) {
        return LD_VALID | (2 * isB + v) | (uint32_t)(b * 32 * 4096 + 64 * idx) << 10;
    }
    void pair(int isB, int b, int idx, uint32_t fk = 0, uint32_t fv = 0) {
        ring(tile(isB, b, idx, 0) | fk);
        ring(tile(isB, b, idx, 1) | fv);
    }
    void qproj(int mask, int layer, uint32_t f) {
        for (int p = 0; p < 3; p++) ring(LD_VALID | (4 + (layer & 1)) | (64 * p) << 10 | (p == 2 ? LD_HALF : 0u) | f);
        if (layer > 0) pending = LD_ANCHOR;
        P.prog[np++] = OP_QPROJ | (mask << 3) | (layer << 5);
        for (int b = 0; b < 2; b++)
            if ((mask >> b) & 1) P.merge[nm++] = MG_Q | (b << 2) | (layer << 3);
    }
    void oproj(int mask, int layer, uint32_t fLast) {
        for (int p = 0; p < 3; p++) ring(LD_VALID | (6 + (layer & 1)) | (16 * p) << 10 | (p == 2 ? fLast : 0u));
        P.prog[np++] = OP_OPROJ | (mask << 3) | (layer << 5);
    }
    void rfload(int from, int to, int isB, int b, int idx0) {
        for (int i = from; i < to; i++) ring(tile(isB, b, idx0 + i / 2, i & 1));
        P.prog[np++] = OP_RFLOAD | (from << 3) | (to << 6);
    }
    void seg(int b, int layer, uint32_t flags, const char* order) {
        uint64_t list = 0;
        for (int n = 0; order[n]; n++) {
            const char c = order[n];
            uint64_t item = 12;
            if (c >= 'a' && c <= 'c') item = 12 | (c - 'a' + 1);
            if (c >= 'A' && c <= 'C') item = 8 | (c - 'A' + 1);
            list |= item << (4 * n);
        }
        P.prog[np++] = OP_SEG | (b << 3) | ((layer & 1) << 4) | (flags & RF);
        P.prog[np++] = (uint32_t)list;
        P.prog[np++] = (uint32_t)(list >> 32);
        P.merge[nm++] = MG_ATTN | (b << 2) | (layer << 3) | ((flags & FIRST) ? 32 : 0) | ((flags & PUB) ? 64 : 0);
    }
};

void build_schedule(Params& P) {
    for (int i = 0; i < kMaxProg; i++) P.prog[i] = OP_END;
    for (int i = 0; i < kMaxMerge; i++) P.merge[i] = MG_END;
    for (int i = 0; i < kMaxLoads; i++) P.loads[i] = 0;
    const uint32_t anchorDelay[kAnchors] = {200, 200, 200, 200, 0};
    const uint32_t anchorCredit[kAnchors] = {kCredit, 2500, 2500, kCredit, 300};
    for (int i = 0; i < kAnchors; i++) {
        P.anchorDelay[i] = anchorDelay[i];
        P.anchorCredit[i] = anchorCredit[i];
    }

    Sched S{P};
    using F = Sched;
    const int keep[2] = {9, 10};
    auto kept = [&](int b, int idx, int v, uint32_t f) { return (2 * (15 - idx) + (1 - v)) < keep[b] ? f : 0u; };
    int nextD[2] = {3, 7}, nextH[2] = {11, 11}, nextK = 11;
    auto fill = [&](int b, int layer, int n, uint32_t flags = 0) {
        for (int i = 0; i < n; i++) S.pair(1, b, nextD[b]++);
        S.seg(b, layer, flags, &"dd"[2 - n]);
    };
    auto mixed = [&](int b, int layer, uint32_t flags, const char* order, int refill0, const int* pos) {
        int tiles = 0, done = 0, dst[6], n = 0;
        for (const char* c = order; *c; c++)
            if (*c >= 'a' && *c <= 'c') { dst[n++] = kRing + 2 * (*c - 'a'); dst[n++] = kRing + 2 * (*c - 'a') + 1; }
        for (const char* c = order; *c; c++) {
            if (*c != 'h' && *c != 'd' && *c != 'k') continue;
            const int idx = *c == 'h' ? nextH[b]++ : *c == 'k' ? nextK++ : nextD[b]++;
            for (int v = 0; v < 2; v++, tiles++) {
                for (; done < n && pos[done] <= tiles; done++) S.slot(F::tile(1, 1, refill0 + done / 2, done & 1) | LD_FAR, dst[done]);
                S.ring(F::tile(1, b, idx, v) | LD_FAR | kept(b, idx, v, *c == 'h' ? LD_HIT : *c == 'k' ? LD_KEEP : 0u));
            }
        }
        S.seg(b, layer, flags, order);
    };

    S.qproj(3, 0, LD_KEEP);
    S.slot(F::tile(0, 1, 0, 0), kRing);
    S.slot(F::tile(0, 1, 0, 1), kRing + 1);
    S.rfload(0, 8, 0, 0, 0);
    S.seg(0, 0, F::RF | F::FIRST | F::PUB, "");
    S.handoff_begin();
    for (int i = 1; i < 4; i++) S.pair(0, 1, i);
    S.seg(1, 0, F::FIRST | F::PUB, "addd");
    S.oproj(3, 0, LD_KEEP);
    for (int i = 0; i < 4; i++) S.slot(F::tile(1, 0, i / 2, i & 1), kRing + i);
    S.qproj(3, 1, LD_KEEP);
    for (int i = 4; i < 6; i++) S.slot(F::tile(1, 0, i / 2, i & 1), kRing + i);
    S.handoff_end();
    for (int i = 3; i < 16; i++) S.pair(1, 0, i, kept(0, i, 0, LD_KEEP), kept(0, i, 1, LD_KEEP));
    S.seg(0, 1, F::FIRST | F::PUB, "dddAdddBdddCdddd");
    S.handoff_begin();
    S.oproj(1, 1, 0);
    fill(1, 1, 2, F::FIRST);
    S.qproj(1, 2, LD_HIT);
    fill(1, 1, 1);
    S.seg(0, 2, F::RF | F::FIRST | F::PUB, "");
    S.rfload(0, 2, 1, 1, 3);
    S.oproj(1, 2, LD_HIT);
    S.rfload(2, 6, 1, 1, 3);
    fill(1, 1, 1);
    S.qproj(1, 3, LD_HIT);
    S.rfload(6, 8, 1, 1, 3);
    S.handoff_end();
    const int pos4[6] = {3, 3, 4, 5, 7, 7};
    mixed(0, 3, F::FIRST, "ahbhchhh", 0, pos4);
    mixed(1, 1, F::RF | F::PUB, "kkABkCkk", 0, nullptr);
    S.handoff_begin();
    S.oproj(2, 1, LD_KEEP);
    fill(0, 3, 2);
    S.qproj(2, 2, 0);
    fill(0, 3, 1);
    for (int i = 0; i < 4; i++) S.pair(0, 1, i);
    S.seg(1, 2, F::FIRST | F::PUB, "dddd");
    fill(0, 3, 1);
    S.oproj(2, 2, 0);
    fill(0, 3, 2);
    S.qproj(2, 3, 0);
    S.handoff_end();
    mixed(0, 3, F::PUB, "dd", 0, nullptr);
    const int pos6[6] = {3, 4, 7, 9, 10, 11};
    nextD[1] = 10;
    mixed(1, 3, F::RF | F::FIRST | F::PUB, "adbhchhAhBhC", 7, pos6);
    S.oproj(3, 3, LD_HIT);
}

typedef CUresult (*EncodeFn)(CUtensorMap*, CUtensorMapDataType, cuuint32_t, void*, const cuuint64_t*,
                             const cuuint64_t*, const cuuint32_t*, const cuuint32_t*, CUtensorMapInterleave,
                             CUtensorMapSwizzle, CUtensorMapL2promotion, CUtensorMapFloatOOBfill);

}

extern "C" void kernel_launch(void* const* d_in, const int* in_sizes, int n_in, void* d_out, int out_size) {
    (void)in_sizes; (void)n_in; (void)out_size;
    Params P;
    void* fn = nullptr;
    cudaDriverEntryPointQueryResult qr;
    cudaGetDriverEntryPoint("cuTensorMapEncodeTiled", &fn, cudaEnableDefault, &qr);
    EncodeFn encode = reinterpret_cast<EncodeFn>(fn);
    auto make_map = [&](int i, void* base, cuuint64_t rows, cuuint64_t rowBytes, cuuint64_t lines, cuuint32_t boxRows,
                        cuuint32_t boxLines) {
        const cuuint64_t dims[3] = {64, rows, lines};
        const cuuint64_t strides[2] = {rowBytes, 128};
        const cuuint32_t box[3] = {64, boxRows, boxLines};
        const cuuint32_t es[3] = {1, 1, 1};
        encode(&P.tm[i], CU_TENSOR_MAP_DATA_TYPE_BFLOAT16, 3, base, dims, strides, box, es, CU_TENSOR_MAP_INTERLEAVE_NONE,
               CU_TENSOR_MAP_SWIZZLE_128B, CU_TENSOR_MAP_L2_PROMOTION_NONE, CU_TENSOR_MAP_FLOAT_OOB_FILL_NONE);
    };
    for (int i = 0; i < 2; i++) {
        void* const* in = d_in + 5 * i;
        make_map(2 * i, in[1], 2 * 32 * 4096, 384, 3, 64, 3);
        make_map(2 * i + 1, in[2], 2 * 32 * 4096, 384, 3, 64, 3);
        make_map(4 + i, in[3], 640, 12288, 96, 64, 3);
        make_map(8 + i, in[3], 640, 12288, 96, 32, 3);
        make_map(6 + i, in[4], 6144, 1280, 10, 16, 10);
    }
    P.x = static_cast<const __nv_bfloat16*>(d_in[0]);
    P.out = static_cast<__nv_bfloat16*>(d_out);
    build_schedule(P);
    cudaFuncSetAttribute(fused_decode_kernel, cudaFuncAttributeMaxDynamicSharedMemorySize, kSmemBytes);
    fused_decode_kernel<<<kCtas, kThreads, kSmemBytes>>>(P);
}
```

```cpp
#include <cuda_runtime.h>
#include <cuda_bf16.h>
#include <cuda.h>
#include <stdint.h>

namespace {

constexpr int kCtas = 128;
constexpr int kThreads = 384;
constexpr int kSlotBytes = 3072;
constexpr int kRing = 3;
constexpr int kSlots = 9;
constexpr int kWRow = 192;

constexpr int kOffWbuf = kSlots * 8 * kSlotBytes;
constexpr int kOffMl = kOffWbuf + 8 * kWRow * 4;
constexpr int kOffCpart = kOffMl + 20 * 4;
constexpr int kOffQf = kOffCpart + 2 * kWRow * 4;
constexpr int kOffXn = kOffQf + 2 * 96 * 4;
constexpr int kOffObf = kOffXn + 2 * 160 * 2;
constexpr int kOffFull = kOffObf + 2 * 48 * 2;
constexpr int kOffEmpty = kOffFull + kSlots * 8;
constexpr int kOffSync = kOffEmpty + kSlots * 8;
constexpr int kOffAnchor = kOffSync + 14 * 8;
constexpr int kOffOwn = kOffAnchor + 8;
constexpr int kSmemBytes = kOffOwn + 32;
static_assert(kSmemBytes <= 232448, "shared memory budget");
constexpr int kBarRows = 0, kBarFree = 8, kBarQ = 16, kBarXn = 32, kBarO = 48;
constexpr int kBarSentQ = 64, kBarSentP = 80, kBarSentY = 96;

constexpr int kMaxProg = 72;
constexpr int kMaxMerge = 32;
constexpr int kMaxLoads = 176;
constexpr int kAnchors = 5;

constexpr uint32_t kTau = 970;
constexpr uint32_t kTauHandoff = 1000;
constexpr uint32_t kTauWo = 833;
constexpr uint32_t kCredit = 700;
constexpr uint32_t kWindow = 3;
constexpr uint32_t kStartWindow = 4, kStartLoads = 10, kStartDelay = 1000;
constexpr uint32_t kLook = 3, kLookFar = 4;
constexpr uint32_t kDelayX = 2200, kDelayP = 1000, kDelayIdle = 3500, kPauseX = 200;

enum : uint32_t { OP_END = 0, OP_QPROJ = 1, OP_RFLOAD = 2, OP_SEG = 3, OP_OPROJ = 4 };
enum : uint32_t { MG_END = 0, MG_ATTN = 1, MG_Q = 2 };
enum : uint32_t {
    LD_KEEP = 1u << 3,
    LD_HANDOFF = 1u << 8,
    LD_VALID = 1u << 9,
    LD_HALF = 1u << 28,
    LD_ANCHOR = 1u << 29,
    LD_FAR = 1u << 30,
    LD_HIT = 1u << 31
};

struct alignas(64) Params {
    CUtensorMap tm[10];
    const __nv_bfloat16* x;
    __nv_bfloat16* out;
    uint32_t anchorDelay[kAnchors], anchorCredit[kAnchors];
    uint32_t prog[kMaxProg];
    uint32_t merge[kMaxMerge];
    uint32_t loads[kMaxLoads];
};

__device__ uint4 g_q[2][32][4][40];
__device__ uint4 g_p[2][32][4][4][18];
constexpr int kAccPackets = 216;
constexpr float kAccDone = 129.f;
constexpr int kAccPad = 2;
__device__ float4 g_acc[2][3][kAccPackets * kAccPad];
constexpr int kOutReplicas = 8;
__device__ float4 g_out[2][kOutReplicas][kAccPackets * kAccPad];

constexpr uint32_t kSpinLimit = 1u << 22;

__device__ __forceinline__ void mbar_init(uint32_t bar, uint32_t count) {
    asm volatile("mbarrier.init.shared::cta.b64 [%0], %1;" ::"r"(bar), "r"(count) : "memory");
}
__device__ __forceinline__ void mbar_arrive(uint32_t bar) {
    asm volatile("mbarrier.arrive.shared::cta.b64 _, [%0];" ::"r"(bar) : "memory");
}
__device__ __forceinline__ bool mbar_test(uint32_t bar, uint32_t parity) {
    uint32_t ok;
    asm volatile(
        "{\n\t.reg .pred p;\n\t"
        "mbarrier.test_wait.parity.shared::cta.b64 p, [%1], %2;\n\t"
        "selp.u32 %0, 1, 0, p;\n\t}"
        : "=r"(ok) : "r"(bar), "r"(parity) : "memory");
    return __all_sync(0xffffffffu, ok);
}
__device__ __forceinline__ void mbar_expect(uint32_t bar, uint32_t bytes) {
    asm volatile("mbarrier.arrive.expect_tx.shared::cta.b64 _, [%0], %1;" ::"r"(bar), "r"(bytes) : "memory");
}
__device__ __forceinline__ void mbar_wait(uint32_t bar, uint32_t parity) {
    uint32_t ok, it = 0;
    do {
        asm volatile(
            "{\n\t.reg .pred p;\n\t"
            "mbarrier.try_wait.parity.shared::cta.b64 p, [%1], %2;\n\t"
            "selp.u32 %0, 1, 0, p;\n\t}"
            : "=r"(ok) : "r"(bar), "r"(parity) : "memory");
        if (++it > kSpinLimit) __trap();
    } while (!ok);
}
__device__ __forceinline__ bool mbar_try(uint32_t bar, uint32_t parity) {
    uint32_t ok;
    asm volatile(
        "{\n\t.reg .pred p;\n\t"
        "mbarrier.try_wait.parity.shared::cta.b64 p, [%1], %2;\n\t"
        "selp.u32 %0, 1, 0, p;\n\t}"
        : "=r"(ok) : "r"(bar), "r"(parity) : "memory");
    return __all_sync(0xffffffffu, ok);
}
__device__ __forceinline__ void mbar_wait_u(uint32_t bar, uint32_t parity) {
    for (uint32_t it = 0; !mbar_try(bar, parity); it++)
        if (it > kSpinLimit) __trap();
}
__device__ __forceinline__ void tma3d(uint32_t dst, const CUtensorMap* tm, int c0, int c1, int c2, uint32_t bar, uint64_t pol) {
    asm volatile(
        "cp.async.bulk.tensor.3d.shared::cluster.global.mbarrier::complete_tx::bytes.L2::cache_hint "
        "[%0], [%1, {%2, %3, %4}], [%5], %6;"
        ::"r"(dst), "l"(tm), "r"(c0), "r"(c1), "r"(c2), "r"(bar), "l"(pol) : "memory");
}
__device__ __forceinline__ void tma3d_prefetch(const CUtensorMap* tm, int c0, int c1, int c2, uint64_t pol) {
    asm volatile("cp.async.bulk.prefetch.tensor.3d.L2.global.L2::cache_hint [%0, {%1, %2, %3}], %4;"
                 ::"l"(tm), "r"(c0), "r"(c1), "r"(c2), "l"(pol) : "memory");
}
__device__ __forceinline__ uint64_t make_policy(bool keep) {
    uint64_t pol;
    if (keep) asm volatile("createpolicy.fractional.L2::evict_normal.b64 %0, 1.0;" : "=l"(pol));
    else      asm volatile("createpolicy.fractional.L2::evict_first.b64 %0, 1.0;" : "=l"(pol));
    return pol;
}
__device__ __forceinline__ void ldsm4(uint32_t (&r)[4], uint32_t addr) {
    asm volatile("ldmatrix.sync.aligned.m8n8.x4.shared.b16 {%0,%1,%2,%3}, [%4];"
                 : "=r"(r[0]), "=r"(r[1]), "=r"(r[2]), "=r"(r[3]) : "r"(addr) : "memory");
}
__device__ __forceinline__ void ldsm4t(uint32_t (&r)[4], uint32_t addr) {
    asm volatile("ldmatrix.sync.aligned.m8n8.x4.trans.shared.b16 {%0,%1,%2,%3}, [%4];"
                 : "=r"(r[0]), "=r"(r[1]), "=r"(r[2]), "=r"(r[3]) : "r"(addr) : "memory");
}
__device__ __forceinline__ void mma16816(float (&c)[4], const uint32_t (&a)[4], uint32_t b0, uint32_t b1) {
    asm volatile("mma.sync.aligned.m16n8k16.row.col.f32.bf16.bf16.f32 {%0,%1,%2,%3}, {%4,%5,%6,%7}, {%8,%9}, {%0,%1,%2,%3};"
                 : "+f"(c[0]), "+f"(c[1]), "+f"(c[2]), "+f"(c[3])
                 : "r"(a[0]), "r"(a[1]), "r"(a[2]), "r"(a[3]), "r"(b0), "r"(b1));
}
__device__ __forceinline__ float bf16r(float v) { return __bfloat162float(__float2bfloat16_rn(v)); }
__device__ __forceinline__ uint32_t pack_bf16(float lo, float hi) {
    uint32_t r;
    asm("cvt.rn.bf16x2.f32 %0, %1, %2;" : "=r"(r) : "f"(hi), "f"(lo));
    return r;
}
__device__ __forceinline__ bool elect() {
    uint32_t p;
    asm volatile("{\n\t.reg .pred e;\n\telect.sync _|e, 0xffffffff;\n\tselp.u32 %0, 1, 0, e;\n\t}" : "=r"(p));
    return p;
}
__device__ __forceinline__ float fast_sqrt(float v) {
    float r;
    asm("sqrt.approx.f32 %0, %1;" : "=f"(r) : "f"(v));
    return r;
}
__device__ __forceinline__ float ex2(float v) {
    float r;
    asm("ex2.approx.ftz.f32 %0, %1;" : "=f"(r) : "f"(v));
    return r;
}
__device__ __forceinline__ void st_packet(uint4* p, uint32_t a, uint32_t b, uint32_t c, uint32_t tag) {
    asm volatile(
        "{\n\t.reg .b64 lo, hi;\n\t.reg .b128 v;\n\t"
        "mov.b64 lo, {%1, %2};\n\tmov.b64 hi, {%3, %4};\n\tmov.b128 v, {lo, hi};\n\t"
        "st.relaxed.gpu.global.b128 [%0], v;\n\t}"
        ::"l"(p), "r"(a), "r"(b), "r"(c), "r"(tag) : "memory");
}
__device__ __forceinline__ void st_packet(uint4* p, float a, float b, float c, uint32_t tag) {
    st_packet(p, __float_as_uint(a), __float_as_uint(b), __float_as_uint(c), tag);
}
__device__ __forceinline__ uint4 ld_packet(const uint4* p) {
    uint4 v;
    asm volatile(
        "{\n\t.reg .b64 lo, hi;\n\t.reg .b128 v;\n\t"
        "ld.relaxed.gpu.global.b128 v, [%4];\n\t"
        "mov.b128 {lo, hi}, v;\n\tmov.b64 {%0, %1}, lo;\n\tmov.b64 {%2, %3}, hi;\n\t}"
        : "=r"(v.x), "=r"(v.y), "=r"(v.z), "=r"(v.w) : "l"(p) : "memory");
    return v;
}
__device__ __forceinline__ void red_packet(float4* p, float a, float b, float c) {
    asm volatile("red.relaxed.gpu.global.add.v4.f32 [%0], {%1, %2, %3, %4};"
                 ::"l"(p), "f"(a), "f"(b), "f"(c), "f"(1.f) : "memory");
}
#define POLL_UNTIL(pause, loads, done)            \
    for (uint32_t it_ = 0;; it_++) {              \
        loads;                                    \
        if (__all_sync(0xffffffffu, done)) break; \
        if (it_ > kSpinLimit) __trap();           \
        if (pause) __nanosleep(pause);            \
    }
__device__ __forceinline__ uint32_t round24(float v) {
    const uint32_t u = __float_as_uint(v);
    return u + ((u & 0x7f800000u) == 0x7f800000u ? 0u : 0x80u);
}
__device__ __forceinline__ void st_packet5(uint4* p, const float* v, uint32_t tag) {
    const uint32_t r0 = round24(v[0]), r1 = round24(v[1]), r2 = round24(v[2]), r3 = round24(v[3]), r4 = round24(v[4]);
    st_packet(p, __byte_perm(r0, r1, 0x5321), __byte_perm(r1, r2, 0x6532), __byte_perm(r2, r3, 0x7653),
              (r4 >> 8) | (tag << 24));
}
__device__ __forceinline__ void add_packet5(float (&a)[5], const uint4& v) {
    a[0] += __uint_as_float(v.x << 8);
    a[1] += __uint_as_float(__funnelshift_r(v.x, v.y, 16) & 0xffffff00u);
    a[2] += __uint_as_float(__funnelshift_r(v.y, v.z, 8) & 0xffffff00u);
    a[3] += __uint_as_float(v.z & 0xffffff00u);
    a[4] += __uint_as_float(v.w << 8);
}
__device__ __forceinline__ uint32_t now_ns() {
    uint32_t t;
    asm volatile("mov.u32 %0, %globaltimer_lo;" : "=r"(t));
    return t;
}
__device__ __forceinline__ int fresh_lane() {
    int lane = threadIdx.x & 31;
    asm volatile("" : "+r"(lane));
    return lane;
}
__device__ __forceinline__ void pause_ns(uint32_t ns) {
    const uint32_t t0 = now_ns();
    while (now_ns() - t0 < ns) __nanosleep(100);
}
__device__ __forceinline__ float bf_lo(uint32_t v) { return __uint_as_float(v << 16); }
__device__ __forceinline__ float bf_hi(uint32_t v) { return __uint_as_float(v & 0xffff0000u); }
__device__ __forceinline__ float warp_sum(float v) {
#pragma unroll
    for (int o = 16; o > 0; o >>= 1) v += __shfl_xor_sync(0xffffffffu, v, o);
    return v;
}

constexpr float kScale = 0.07216878364870322f * 1.4426950408889634f;

struct Attn {
    float m, l;
    float acc[3][4];
};

__device__ __forceinline__ uint32_t probability(Attn& st, float s) {
    const float e = ex2(s - st.m);
    st.l += e;
    const float hi = bf16r(e);
    const uint32_t hl = pack_bf16(hi, e - hi);
    uint32_t pv;
    asm volatile("movmatrix.sync.aligned.m8n8.trans.b16 %0, %1;" : "=r"(pv) : "r"(hl));
    return pv;
}

__device__ __forceinline__ uint32_t softmax_step(Attn& st, float s) {
    if (__any_sync(0xffffffffu, s > st.m)) {
        float mx = fmaxf(s, __shfl_xor_sync(0xffffffffu, s, 4));
        mx = fmaxf(mx, __shfl_xor_sync(0xffffffffu, mx, 8));
        mx = fmaxf(mx, __shfl_xor_sync(0xffffffffu, mx, 16));
        mx = fmaxf(mx, st.m);
        const float corr = ex2(st.m - mx);
        st.m = mx;
        st.l *= corr;
#pragma unroll
        for (int a = 0; a < 3; a++)
#pragma unroll
            for (int i = 0; i < 4; i++) st.acc[a][i] *= corr;
    }
    return probability(st, s);
}

__global__ void __launch_bounds__(kThreads, 1)
fused_decode_kernel(const __grid_constant__ Params P) {
    extern __shared__ __align__(1024) unsigned char smem[];
    const uint32_t sbase = (uint32_t)__cvta_generic_to_shared(smem);
    const uint32_t sync0 = sbase + kOffSync;
    float* const wbuf = reinterpret_cast<float*>(smem + kOffWbuf);

    const int lane = threadIdx.x & 31;
    const int w = __shfl_sync(0xffffffffu, threadIdx.x >> 5, 0);
    const int cta = blockIdx.x;
    const int h = cta >> 2, jq = cta & 3;

    if (w >= 10) {
        const int i0 = 80 * (w - 10) + lane;
#pragma unroll
        for (int i = 0; i < 3; i++)
            if (i < 2 || lane < 16)
                asm volatile("cp.async.cg.shared.global [%0], [%1], 16;"
                             ::"r"(sbase + kOffWbuf + 16 * (i0 + 32 * i)), "l"(reinterpret_cast<const uint4*>(P.x) + i0 + 32 * i) : "memory");
    }
    if (elect()) {
        if (w == 8) {
#pragma unroll
            for (int i = 0; i < kSlots; i++) {
                mbar_init(sbase + kOffFull + 8 * i, 1);
                mbar_init(sbase + kOffEmpty + 8 * i, 8);
            }
        } else if (w == 9) {
#pragma unroll
            for (int i = 0; i < 10; i++) asm volatile("prefetch.tensormap [%0];" ::"l"(&P.tm[i]) : "memory");
        } else if (w == 10) {
#pragma unroll
            for (int i = 0; i < 14; i++) mbar_init(sync0 + 8 * i, (8 * i == kBarRows || 8 * i >= kBarSentY) ? 8 : 1);
        }
        if (w != 9) asm volatile("fence.mbarrier_init.release.cluster;" ::: "memory");
    }
    __syncwarp();
    if (w == 8) {
        asm volatile("bar.arrive 1, %0;" ::"n"(kThreads) : "memory");
    } else {
        asm volatile("bar.sync 1, %0;" ::"n"(kThreads) : "memory");
    }

    if (w < 8) {
        asm volatile("setmaxnreg.inc.sync.aligned.u32 232;");
        const uint32_t full0 = sbase + kOffFull;
        const uint32_t frag0 = sbase + w * 1024 + (lane & 7) * 128 + (((lane >> 3) ^ (lane & 7)) << 4), frag1 = frag0 ^ 64;
        auto frag_addr = [&](uint32_t s, int k) { return ((k & 1) ? frag1 : frag0) + s * (8 * kSlotBytes) + (k >> 1) * 8192; };
        uint32_t par = 0, rpos = 0, nrows = 0;
        auto wait_tile = [&](uint32_t s) { mbar_wait(full0 + 8 * s, (par >> s) & 1u); };
        auto tile_ready = [&](uint32_t s) { return mbar_test(full0 + 8 * s, (par >> s) & 1u); };
        auto release = [&](uint32_t s) {
            par ^= 1u << s;
            __syncwarp();
            if (elect()) mbar_arrive(full0 + 8 * s + (kOffEmpty - kOffFull));
        };
        auto ring_release = [&]() {
            release(rpos);
            if (++rpos == kRing) rpos = 0;
        };
        auto row_acquire = [&]() { mbar_wait(sync0 + kBarFree, (nrows & 1) ^ 1); };
        auto row_publish = [&]() {
            __syncwarp();
            if (elect()) mbar_arrive(sync0 + kBarRows);
            nrows++;
        };

        uint32_t rf[8][6][4];
#pragma unroll
        for (int i = 0; i < 8; i++)
#pragma unroll
            for (int s = 0; s < 6; s++)
#pragma unroll
                for (int k = 0; k < 4; k++) rf[i][s][k] = 0;

#pragma unroll 1
        for (int pc = 0;; pc++) {
            const uint32_t op = P.prog[pc];
            const uint32_t kind = op & 7u;
            if (kind == OP_END) break;
            const int lane = fresh_lane();
            const int g = lane >> 2, t = lane & 3;
            float* const row = wbuf + w * kWRow;

            if (kind == OP_SEG) {
                const uint32_t b = (op >> 3) & 1u;
                mbar_wait(sync0 + kBarQ + 8 * b, (op >> 4) & 1u);
                const uint2* qf = reinterpret_cast<const uint2*>(smem + kOffQf) + b * 48 + (lane & 7);
                Attn st;
                st.m = -INFINITY; st.l = 0.f;
#pragma unroll
                for (int a = 0; a < 3; a++)
#pragma unroll
                    for (int i = 0; i < 4; i++) st.acc[a][i] = 0.f;

                if (op & (1u << 7)) {
                    float c[4][4] = {};
#pragma unroll
                    for (int k = 0; k < 6; k++) {
                        const uint2 q = qf[8 * k];
#pragma unroll
                        for (int i = 0; i < 4; i++) mma16816(c[i], rf[2 * i][k], q.x, q.y);
                    }
                    float sc[4];
#pragma unroll
                    for (int i = 0; i < 4; i++) sc[i] = (c[i][0] + c[i][3]) * kScale;
                    float mx = fmaxf(fmaxf(sc[0], sc[1]), fmaxf(sc[2], sc[3]));
                    mx = fmaxf(mx, __shfl_xor_sync(0xffffffffu, mx, 4));
                    mx = fmaxf(mx, __shfl_xor_sync(0xffffffffu, mx, 8));
                    st.m = fmaxf(mx, __shfl_xor_sync(0xffffffffu, mx, 16));
                    uint32_t pv[4];
#pragma unroll
                    for (int i = 0; i < 4; i++) pv[i] = probability(st, sc[i]);
#pragma unroll
                    for (int i = 0; i < 4; i++)
#pragma unroll
                        for (int k = 0; k < 6; k++)
                            mma16816(st.acc[k >> 1], rf[2 * i + 1][k], (g >> 1) == 2 * (k & 1) ? pv[i] : 0u,
                                     (g >> 1) == 2 * (k & 1) + 1 ? pv[i] : 0u);
                }

                uint32_t lo = P.prog[pc + 1], hi = P.prog[pc + 2];
                pc += 2;
                bool haveK = false;
#pragma unroll 1
                while (lo & 15u) {
                    const bool rel = lo & 4u;
                    uint32_t sK = kRing - 2 + 2 * (lo & 3u), sV = sK + 1;
                    if (!(lo & 3u)) {
                        sK = rpos;
                        sV = rpos == kRing - 1 ? 0 : rpos + 1;
                        rpos = sV == kRing - 1 ? 0 : sV + 1;
                    }
                    lo = __funnelshift_r(lo, hi, 4);
                    hi >>= 4;
                    if (!haveK) wait_tile(sK);
                    const bool haveV = tile_ready(sV);
                    float c[2][4] = {};
#pragma unroll
                    for (int k = 0; k < 6; k++) {
                        uint32_t a[4];
                        ldsm4(a, frag_addr(sK, k));
                        const uint2 q = qf[8 * k];
                        mma16816(c[k & 1], a, q.x, q.y);
                    }
                    if (rel) release(sK);
                    const uint32_t pv = softmax_step(st, ((c[0][0] + c[0][3]) + (c[1][0] + c[1][3])) * kScale);
                    if (!haveV) wait_tile(sV);
                    haveK = tile_ready((lo & 3u) ? kRing - 2 + 2 * (lo & 3u) : rpos);
#pragma unroll
                    for (int k = 0; k < 6; k++) {
                        uint32_t a[4];
                        ldsm4t(a, frag_addr(sV, k));
                        mma16816(st.acc[k >> 1], a, (g >> 1) == 2 * (k & 1) ? pv : 0u, (g >> 1) == 2 * (k & 1) + 1 ? pv : 0u);
                    }
                    if (rel) release(sV);
                }

                float l = st.l;
                l += __shfl_xor_sync(0xffffffffu, l, 4);
                l += __shfl_xor_sync(0xffffffffu, l, 8);
                l += __shfl_xor_sync(0xffffffffu, l, 16);
                row_acquire();
#pragma unroll
                for (int a = 0; a < 3; a++) {
                    row[64 * a + 16 * t + g] = st.acc[a][0] + st.acc[a][1];
                    row[64 * a + 16 * t + g + 8] = st.acc[a][2] + st.acc[a][3];
                }
                if (lane == 0) { wbuf[8 * kWRow + w] = st.m; wbuf[8 * kWRow + 8 + w] = l; }
                row_publish();
            } else if (kind == OP_RFLOAD) {
#pragma unroll 1
                for (uint32_t tile = (op >> 3) & 7u; tile < (op >> 6); tile++) {
                    wait_tile(rpos);
#pragma unroll
                    for (int i = 0; i < 8; i++) {
                        if (tile == i) {
#pragma unroll
                            for (int k = 0; k < 6; k++) {
                                if (i & 1) ldsm4t(rf[i][k], frag_addr(rpos, k));
                                else ldsm4(rf[i][k], frag_addr(rpos, k));
                            }
                        }
                    }
                    ring_release();
                }
            } else if (kind == OP_QPROJ) {
                const uint32_t mask = (op >> 3) & 3u;
#pragma unroll 1
                for (uint32_t b = 0; b < 2; b++)
                    if ((mask >> b) & 1u) mbar_wait(sync0 + kBarXn + 8 * b, (op >> 5) & 1u);
                const uint32_t bb = mask == 3u ? (g & 1) : (mask >> 1);
                const uint32_t* xs = reinterpret_cast<const uint32_t*>(smem + kOffXn) + bb * 80 + 4 * w + t;
                float acc[3][4] = {};
#pragma unroll 1
                for (int p = 0; p < 3; p++) {
                    wait_tile(rpos);
                    if (p < 2 || w < 4) {
                        const uint32_t xv = xs[32 * p];
                        const uint32_t shrink = p == 2 ? 4096 : 0;
#pragma unroll
                        for (int k = 0; k < 6; k++) {
                            uint32_t a[4];
                            ldsm4t(a, frag_addr(rpos, k) - (k >> 1) * shrink);
                            mma16816(acc[k >> 1], a, (g >> 1) == 2 * (k & 1) ? xv : 0u, (g >> 1) == 2 * (k & 1) + 1 ? xv : 0u);
                        }
                    }
                    ring_release();
                }
#pragma unroll 1
                for (uint32_t b = 0; b < 2; b++) {
                    if (!((mask >> b) & 1u)) continue;
                    row_acquire();
#pragma unroll
                    for (int a = 0; a < 3; a++) {
                        row[64 * a + 16 * t + g] = b ? acc[a][1] : acc[a][0];
                        row[64 * a + 16 * t + g + 8] = b ? acc[a][3] : acc[a][2];
                    }
                    row_publish();
                }
            } else {
                const uint32_t mask = (op >> 3) & 3u;
                const uint32_t bb = mask == 3u ? (g & 1) : (mask >> 1);
                const uint32_t* ob = reinterpret_cast<const uint32_t*>(smem + kOffObf) + bb * 24 + t;
                const uint32_t roff = ((lane & 7) + 8 * (lane >> 4)) * 128 + ((((lane >> 3) & 1) ^ (lane & 7)) << 4);
                uint32_t sl[3];
#pragma unroll
                for (int p = 0; p < 3; p++) {
                    sl[p] = rpos;
                    if (++rpos == kRing) rpos = 0;
                }
                auto frag = [&](uint32_t (&a)[4], int p, int mt) {
                    ldsm4t(a, ((sbase + sl[p] * 8 * kSlotBytes + roff) ^ (((5 * w + mt) & 3) << 5)) + ((5 * w + mt) >> 2) * 2048);
                };
                uint32_t a0[5][4];
                wait_tile(sl[0]);
#pragma unroll
                for (int mt = 0; mt < 5; mt++) frag(a0[mt], 0, mt);
                release(sl[0]);
                wait_tile(sl[1]);
                wait_tile(sl[2]);
                row_acquire();
                if (mask & 1u) mbar_wait(sync0 + kBarO, (op >> 5) & 1u);
                if (mask & 2u) mbar_wait(sync0 + kBarO + 8, (op >> 5) & 1u);
                float c[3][4] = {};
#pragma unroll
                for (int p = 0; p < 3; p++) {
                    const uint32_t b0 = ob[8 * p], b1 = ob[8 * p + 4];
#pragma unroll
                    for (int mt = 0; mt < 5; mt++) {
                        if (p > 0) frag(a0[mt], p, mt);
                        const bool on = (g >> 1) == (mt & 3);
                        mma16816(c[mt == 4 ? 2 : (mt & 1)], a0[mt], on ? b0 : 0u, on ? b1 : 0u);
                    }
                    if (p > 0) release(sl[p]);
                }
                row[16 * t + g] = c[0][0] + c[1][0]; row[80 + 16 * t + g] = c[0][1] + c[1][1];
                row[16 * t + g + 8] = c[0][2] + c[1][2]; row[80 + 16 * t + g + 8] = c[0][3] + c[1][3];
                if (t == 0) {
                    row[64 + g] = c[2][0]; row[144 + g] = c[2][1];
                    row[72 + g] = c[2][2]; row[152 + g] = c[2][3];
                }
                __syncwarp();
                if (lane < 27) {
                    const bool last = ((op >> 5) & 3u) == 3u;
                    float4* dst = (last ? g_out[0][cta % kOutReplicas] : g_acc[0][(op >> 5) & 3u]) + (27 * w + lane) * kAccPad;
                    const float* y = row + 3 * lane;
                    if (mask & 1u) red_packet(dst, y[0], y[1], lane < 26 ? y[2] : 0.f);
                    if (mask & 2u) red_packet(dst + (last ? kOutReplicas : 3) * kAccPad * kAccPackets, y[80], y[81], lane < 26 ? y[82] : 0.f);
                }
                __syncwarp();
                if (lane < 2 && ((mask >> lane) & 1u)) mbar_arrive(sync0 + kBarSentY + 8 * lane);
            }
        }
    } else {
        asm volatile("setmaxnreg.dec.sync.aligned.u32 40;");
        if (w == 8) {
            if (elect()) {
#pragma unroll
                for (int p = 0; p < kRing; p++) {
                    const CUtensorMap* tm = &P.tm[p == 2 ? 8 : 4];
                    mbar_expect(sbase + kOffFull + 8 * p, p == 2 ? 4 * kSlotBytes : 8 * kSlotBytes);
                    tma3d(sbase + p * 8 * kSlotBytes, tm, 0, 160 * jq + 64 * p, 3 * h, sbase + kOffFull + 8 * p, make_policy(false));
                    tma3d_prefetch(tm, 0, 160 * jq + 64 * p, 3 * h, make_policy(true));
                }
            }
            __syncwarp();
            const int rowA = h * 4096 + 3072 + 256 * jq, rowB = h * 4096 + 1024 * jq;
            const int rowWq = 160 * jq, rowWo = 192 * h + 48 * jq;
            const uint64_t polKeep = make_policy(true), polStream = make_policy(false);
            const uint32_t rot = 64u * 11u * ((h & 3) + ((h >> 2) & 3) + (h >> 4));
            auto coord = [&](uint32_t e) {
                const uint32_t off = (e >> 10) & 0x3ffffu;
                const uint32_t offB = (off & ~0x3ffu) + ((off + rot) & 0x3c0u) + rowB;
                return (int)((e & 4u) ? off + ((e & 2u) ? rowWo : rowWq) : ((e & 2u) ? offB : off + rowA));
            };
            auto line = [&](uint32_t e) { return (e & 6u) == 4u ? 3 * h : 0; };
            auto map = [&](uint32_t e) { return &P.tm[(e & 7u) + ((e >> 26) & 4u)]; };
            auto interval = [&](uint32_t e) {
                return (e & 6u) == 6u ? kTauWo : ((e & LD_HANDOFF) ? kTauHandoff : kTau) >> ((e >> 28) & 1u);
            };
            uint32_t par = 7u, recent = 0x3012u, m = 0, na = 0, credit = kCredit, next = now_ns() + kStartDelay;
            auto landed = [&](uint32_t s) { return mbar_test(sbase + kOffFull + 8 * s, ((par >> s) & 1u) ^ 1u); };
            uint32_t e = P.loads[kRing];
            int c1 = coord(e);
#pragma unroll 1
            for (uint32_t n = kRing; e & LD_VALID; n++) {
                const uint32_t s = (e >> 4) & 15u;
                const uint32_t full = sbase + kOffFull + 8 * s;
                const uint32_t enext = P.loads[n + 1];
                if (m < n) m = n;
                for (uint32_t it = 0; !mbar_test(full + (kOffEmpty - kOffFull), ((par >> s) & 1u) ^ 1u); it++) {
                    if (it > 16 * kSpinLimit) __trap();
                    const uint32_t f = P.loads[m];
                    if (m >= n + ((e & LD_FAR) ? kLookFar : kLook) || !(f & LD_VALID)) continue;
                    if (f & LD_HIT) { m++; continue; }
                    const uint32_t now = now_ns();
                    if ((int)(now - next) >= 0 && landed(recent & 15u)) {
                        if (elect()) tma3d_prefetch(map(f), 0, coord(f), line(f), polStream);
                        next = now + interval(f);
                        m++;
                    }
                }
                if (e & LD_ANCHOR) {
                    const uint32_t t0 = __shfl_sync(0xffffffffu, *reinterpret_cast<volatile uint32_t*>(smem + kOffAnchor), 0) + P.anchorDelay[na];
                    if (m <= n || (int)(t0 - next) > 0) next = t0;
                    credit = P.anchorCredit[na++];
                }
                if (!(e & LD_HIT) && m <= n) {
                    const uint32_t o = (recent >> (4 * (n < kStartLoads ? kStartWindow : kWindow) - 4)) & 15u;
                    if (o != s) mbar_wait_u(sbase + kOffFull + 8 * o, ((par >> o) & 1u) ^ 1u);
                    uint32_t now = now_ns();
                    while ((int)(now - next) < 0) now = now_ns();
                    if ((int)(now - credit - next) > 0) next = now - credit;
                    next += interval(e);
                    recent = (recent << 4) | s;
                }
                if (elect()) {
                    mbar_expect(full, (e & 6u) == 6u ? 20480 : (8 * kSlotBytes) >> ((e >> 28) & 1u));
                    tma3d(sbase + s * 8 * kSlotBytes, map(e), 0, c1, line(e), full, polStream);
                    if (e & LD_KEEP) tma3d_prefetch(map(e), 0, c1, line(e), polKeep);
                }
                par ^= 1u << s;
                e = enext;
                c1 = coord(e);
            }
        } else {
            if (w == 9) {
#pragma unroll 1
                for (int n = 0;; n++) {
                    const uint32_t job = P.merge[n];
                    if ((job & 3u) == MG_END) break;
                    const uint32_t b = (job >> 2) & 1u;
                    const uint32_t tag = 1 + ((job >> 3) & 3u);
                    mbar_wait(sync0 + kBarRows, n & 1);
                    if ((job & 3u) == MG_Q) {
                        float o[5] = {}, e[5] = {};
                        const float* ext = wbuf + 2 * (lane & 3) * kWRow + 5 * min(32 + (lane >> 2), 38);
#pragma unroll
                        for (int k = 0; k < 5; k++) e[k] = ext[k] + ext[kWRow + k];
#pragma unroll
                        for (int i = 0; i < 8; i++)
#pragma unroll
                            for (int k = 0; k < 5; k++) o[k] += wbuf[i * kWRow + 5 * lane + k];
                        st_packet5(&g_q[b][h][jq][lane], o, tag);
#pragma unroll
                        for (int k = 0; k < 5; k++) {
                            e[k] += __shfl_xor_sync(0xffffffffu, e[k], 1);
                            e[k] += __shfl_xor_sync(0xffffffffu, e[k], 2);
                        }
                        if ((lane & 3) == 0) st_packet5(&g_q[b][h][jq][32 + (lane >> 2)], e, tag);
                        __syncwarp();
                        if (lane == 0) mbar_arrive(sync0 + kBarSentQ + 8 * b);
                    } else {
                        float2* cp = reinterpret_cast<float2*>(smem + kOffCpart) + b * (kWRow / 2) + 3 * lane;
                        float2* cml = reinterpret_cast<float2*>(smem + kOffMl + 64) + b;
                        const float4* ml = reinterpret_cast<const float4*>(smem + kOffMl);
                        const bool merge = !(job & 32u);
                        const float2 pml = merge ? *cml : make_float2(-INFINITY, 0.f);
                        const float4 m0 = ml[0], m1 = ml[1];
                        float sc[8] = {m0.x, m0.y, m0.z, m0.w, m1.x, m1.y, m1.z, m1.w};
                        const float M = fmaxf(fmaxf(fmaxf(fmaxf(sc[0], sc[1]), fmaxf(sc[2], sc[3])),
                                                    fmaxf(fmaxf(sc[4], sc[5]), fmaxf(sc[6], sc[7]))), pml.x);
#pragma unroll
                        for (int i = 0; i < 8; i++) sc[i] = ex2(sc[i] - M);
                        const float ps = ex2(pml.x - M);
                        float2 o[3];
#pragma unroll
                        for (int k = 0; k < 3; k++) {
                            o[k] = merge ? cp[k] : make_float2(0.f, 0.f);
                            o[k].x *= ps; o[k].y *= ps;
                        }
#pragma unroll
                        for (int i = 0; i < 8; i++)
#pragma unroll
                            for (int k = 0; k < 3; k++) {
                                const float2 v = reinterpret_cast<const float2*>(wbuf)[i * (kWRow / 2) + 3 * lane + k];
                                o[k].x = fmaf(v.x, sc[i], o[k].x);
                                o[k].y = fmaf(v.y, sc[i], o[k].y);
                            }
                        const float4 l0 = ml[2], l1 = ml[3];
                        const float L = fmaf(pml.y, ps, ((l0.x * sc[0] + l0.y * sc[1]) + (l0.z * sc[2] + l0.w * sc[3])) +
                                                        ((l1.x * sc[4] + l1.y * sc[5]) + (l1.z * sc[6] + l1.w * sc[7])));
                        if (job & 64u) {
                            uint4* dst = &g_p[b][h][lane >> 3][jq][2 * (lane & 7)];
                            st_packet(dst, o[0].x, o[0].y, o[1].x, tag);
                            st_packet(dst + 1, o[1].y, o[2].x, o[2].y, tag);
                            if (lane < 8) st_packet(&g_p[b][h][lane >> 1][jq][16 + (lane & 1)], M, L, 0.f, tag);
                            if (lane == 0) mbar_arrive(sync0 + kBarSentP + 8 * b);
                        } else {
#pragma unroll
                            for (int k = 0; k < 3; k++) cp[k] = o[k];
                            __syncwarp();
                            if (lane == 0) *cml = make_float2(M, L);
                        }
                    }
                    __syncwarp();
                    if (lane == 0) mbar_arrive(sync0 + kBarFree);
                }
            } else {
                const uint32_t b = w - 10;
                __nv_bfloat16* const xn = reinterpret_cast<__nv_bfloat16*>(smem + kOffXn) + b * 160;
                __nv_bfloat16* const qd = reinterpret_cast<__nv_bfloat16*>(smem + kOffQf) + b * 192;
                __nv_bfloat16* const ob = reinterpret_cast<__nv_bfloat16*>(smem + kOffObf) + b * 48;
                uint2* const own = reinterpret_cast<uint2*>(smem + kOffOwn) + 2 * b;
#pragma unroll 1
                for (uint32_t layer = 0; layer < 4; layer++) {
                    const uint32_t tag = layer + 1;
                    {
                        int lane = fresh_lane();
                        uint32_t x01[7], x2[7];
                        if (layer == 0) {
                            const uint4* stage = reinterpret_cast<const uint4*>(wbuf) + 80 * b;
                            asm volatile("cp.async.wait_all;" ::: "memory");
                            __syncwarp();
#pragma unroll
                            for (int i = 0; i < 7; i++) {
                                const int p = lane + 32 * i, u = p % 27;
                                const unsigned short* xp = reinterpret_cast<const unsigned short*>(stage) + (p / 27) * 80 + 3 * u;
                                x01[i] = p < kAccPackets ? xp[0] | ((uint32_t)xp[1] << 16) : 0u;
                                x2[i] = (p < kAccPackets && u < 26) ? xp[2] : 0u;
                            }
                        } else {
                            mbar_wait(sync0 + kBarSentY + 8 * b, (layer - 1) & 1);
                            pause_ns(kDelayX);
                            uint4 v[7];
                            const uint4* src = reinterpret_cast<const uint4*>(&g_acc[b][layer - 1][lane * kAccPad]);
                            const uint32_t done = __float_as_uint(kAccDone);
                            POLL_UNTIL(kPauseX, v[0] = ld_packet(src + (27 * (cta & 7) + min(lane, 26) - lane) * kAccPad), v[0].w == done);
                            POLL_UNTIL(kPauseX,
                                v[0] = ld_packet(src); v[1] = ld_packet(src + 32 * kAccPad); v[2] = ld_packet(src + 64 * kAccPad);
                                v[3] = ld_packet(src + 96 * kAccPad); v[4] = ld_packet(src + 128 * kAccPad);
                                v[5] = ld_packet(src + 160 * kAccPad); v[6] = ld_packet(src + (lane < 24 ? 192 * kAccPad : 0)),
                                v[0].w == done && v[1].w == done && v[2].w == done && v[3].w == done && v[4].w == done &&
                                    v[5].w == done && v[6].w == done);
#pragma unroll
                            for (int i = 0; i < 7; i++) {
                                x01[i] = pack_bf16(__uint_as_float(v[i].x), __uint_as_float(v[i].y));
                                x2[i] = pack_bf16(__uint_as_float(v[i].z), 0.f);
                            }
                            if (lane >= 24) x01[6] = x2[6] = 0u;
                        }
#pragma unroll
                        for (int i = 0; i < 7; i++) {
                            const int p = lane + 32 * i;
                            if ((p & 127) == cta && p < kAccPackets) {
                                own[i >> 2] = make_uint2(x01[i], x2[i]);
                            }
                        }
                        float sum = 0.f;
#pragma unroll
                        for (int i = 0; i < 7; i++) sum += (bf_lo(x01[i]) + bf_hi(x01[i])) + bf_lo(x2[i]);
                        const float mean = warp_sum(sum) * (1.f / 640.f);
                        float sq = 0.f;
#pragma unroll
                        for (int i = 0; i < 7; i++) {
                            const bool none = i == 6 && lane >= 24;
                            const float d0 = none ? 0.f : bf_lo(x01[i]) - mean, d1 = none ? 0.f : bf_hi(x01[i]) - mean;
                            const bool last = lane == 26 - 5 * i || lane == 53 - 5 * i;
                            const float d2 = (none || last) ? 0.f : bf_lo(x2[i]) - mean;
                            sq += fmaf(d0, d0, fmaf(d1, d1, d2 * d2));
                        }
                        const float var = warp_sum(sq) * (1.f / 640.f);
                        const float meanb = bf16r(mean);
                        const float rden = __fdividef(1.f, bf16r(fast_sqrt(bf16r(bf16r(var) + 1e-5f))));
#pragma unroll
                        for (int i = 0; i < 7; i++) {
                            const uint32_t q = lane + 32 * i - 54 * jq;
                            if (q < 54u) {
                                const int c = 3 * q - (q >= 27u);
                                xn[c] = __float2bfloat16_rn(bf16r(bf_lo(x01[i]) - meanb) * rden);
                                xn[c + 1] = __float2bfloat16_rn(bf16r(bf_hi(x01[i]) - meanb) * rden);
                                if (q != 26u && q != 53u) xn[c + 2] = __float2bfloat16_rn(bf16r(bf_lo(x2[i]) - meanb) * rden);
                            }
                        }
                        if (lane == 0) *reinterpret_cast<volatile uint32_t*>(smem + kOffAnchor) = now_ns();
                        __syncwarp();
                        if (lane == 0) mbar_arrive(sync0 + kBarXn + 8 * b);
                        if (layer >= 2 && lane < 4 && cta + 128 * (lane >> 1) < kAccPackets)
                            g_acc[b][layer - 2][(cta + 128 * (lane >> 1)) * kAccPad + (lane & 1)] = make_float4(0.f, 0.f, 0.f, 0.f);
                        __syncwarp();
                    }
                    {
                        const int lane = fresh_lane();
                        mbar_wait(sync0 + kBarSentQ + 8 * b, layer & 1);
                        if (layer == 0 || (layer == 1 && b == 1)) pause_ns(kDelayIdle);
                        uint4 v[5];
                        const uint4* src = &g_q[b][h][0][lane];
                        const uint4* ext = &g_q[b][h][lane & 3][lane < 28 ? 32 + (lane >> 2) : 38];
                        POLL_UNTIL(0,
                            v[0] = ld_packet(src); v[1] = ld_packet(src + 40); v[2] = ld_packet(src + 80);
                            v[3] = ld_packet(src + 120); v[4] = ld_packet(ext),
                            (v[0].w >> 24) == tag && (v[1].w >> 24) == tag && (v[2].w >> 24) == tag &&
                                (v[3].w >> 24) == tag && (v[4].w >> 24) == tag);
                        __syncwarp();
                        auto store_q = [&](int d, float q) {
                            qd[(d & ~31) + ((d >> 3) & 1) * 16 + ((d >> 1) & 3) * 4 + ((d >> 4) & 1) * 2 + (d & 1)] =
                                __float2bfloat16_rn(q);
                        };
                        float a[5] = {};
#pragma unroll
                        for (int i = 0; i < 4; i++) add_packet5(a, v[i]);
#pragma unroll
                        for (int k = 0; k < 5; k++) store_q(5 * lane + k, a[k]);
                        float e[5] = {};
                        add_packet5(e, v[4]);
#pragma unroll
                        for (int k = 0; k < 5; k++) {
                            e[k] += __shfl_xor_sync(0xffffffffu, e[k], 1);
                            e[k] += __shfl_xor_sync(0xffffffffu, e[k], 2);
                            const int d = 160 + 5 * (lane >> 2) + k;
                            if ((lane & 3) == 0 && d < 192) store_q(d, e[k]);
                        }
                        __syncwarp();
                        if (lane == 0) mbar_arrive(sync0 + kBarQ + 8 * b);
                    }
                    {
                        const int lane = fresh_lane();
                        mbar_wait(sync0 + kBarSentP + 8 * b, layer & 1);
                        pause_ns((b == 0 && (layer == 0 || layer == 3)) ? kDelayIdle : (layer == 3 ? 0 : kDelayP));
                        uint4 v0, v1, ml;
                        const uint4* src = &g_p[b][h][jq][2 * (lane >> 4)][lane & 15];
                        const uint4* mls = &g_p[b][h][jq][lane & 3][16];
                        POLL_UNTIL(0, v0 = ld_packet(src); v1 = ld_packet(src + 18); ml = ld_packet(mls),
                                   v0.w == tag && v1.w == tag && ml.w == tag);
                        __syncwarp();
                        const float mi = __uint_as_float(ml.x);
                        float M = fmaxf(mi, __shfl_xor_sync(0xffffffffu, mi, 1));
                        M = fmaxf(M, __shfl_xor_sync(0xffffffffu, M, 2));
                        const float sc = ex2(mi - M);
                        float L = __uint_as_float(ml.y) * sc;
                        L += __shfl_xor_sync(0xffffffffu, L, 1);
                        L += __shfl_xor_sync(0xffffffffu, L, 2);
                        const float s0 = __shfl_sync(0xffffffffu, sc, 2 * (lane >> 4));
                        const float s1 = __shfl_sync(0xffffffffu, sc, 2 * (lane >> 4) + 1);
                        float o0 = fmaf(__uint_as_float(v0.x), s0, __uint_as_float(v1.x) * s1);
                        float o1 = fmaf(__uint_as_float(v0.y), s0, __uint_as_float(v1.y) * s1);
                        float o2 = fmaf(__uint_as_float(v0.z), s0, __uint_as_float(v1.z) * s1);
                        o0 += __shfl_xor_sync(0xffffffffu, o0, 16);
                        o1 += __shfl_xor_sync(0xffffffffu, o1, 16);
                        o2 += __shfl_xor_sync(0xffffffffu, o2, 16);
                        if (lane < 16) {
                            ob[3 * lane] = __float2bfloat16_rn(__fdividef(o0, L));
                            ob[3 * lane + 1] = __float2bfloat16_rn(__fdividef(o1, L));
                            ob[3 * lane + 2] = __float2bfloat16_rn(__fdividef(o2, L));
                        }
                        __syncwarp();
                        if (lane == 0) mbar_arrive(sync0 + kBarO + 8 * b);
                        const int p = cta + 128 * lane;
                        if (p < kAccPackets) {
                            const uint2 v = own[lane];
                            red_packet((layer == 3 ? g_out[b][0] : g_acc[b][layer]) + p * kAccPad, bf_lo(v.x), bf_hi(v.x), bf_lo(v.y));
                        }
                    }
                }
                {
                    mbar_wait(sync0 + kBarSentY + 8 * b, 1);
                    const int p = cta + 128 * ((lane / kOutReplicas) & 1), r = lane % kOutReplicas;
                    float4* src = &g_out[b][r][(p < kAccPackets ? p : cta) * kAccPad];
                    const float want = kCtas / kOutReplicas + (r == 0);
                    uint4 v;
                    for (uint32_t it = 0;; it++) {
                        v = ld_packet(reinterpret_cast<const uint4*>(src));
                        if (__all_sync(0xffffffffu, v.w == __float_as_uint(want))) break;
                        if (it > kSpinLimit) __trap();
                    }
                    float o0 = __uint_as_float(v.x), o1 = __uint_as_float(v.y), o2 = __uint_as_float(v.z);
#pragma unroll
                    for (int o = 1; o < kOutReplicas; o <<= 1) {
                        o0 += __shfl_xor_sync(0xffffffffu, o0, o);
                        o1 += __shfl_xor_sync(0xffffffffu, o1, o);
                        o2 += __shfl_xor_sync(0xffffffffu, o2, o);
                    }
                    if (lane < 2 * kOutReplicas && p < kAccPackets) {
                        if (r < 3 - (p % 27 == 26))
                            P.out[b * 640 + (p / 27) * 80 + 3 * (p % 27) + r] = __float2bfloat16_rn(r == 0 ? o0 : r == 1 ? o1 : o2);
                        *src = make_float4(0.f, 0.f, 0.f, 0.f);
                        if (r == 0) g_acc[b][2][p * kAccPad] = make_float4(0.f, 0.f, 0.f, 0.f);
                    }
                }
            }
        }
    }
}


struct Sched {
    Params& P;
    int np = 0, nm = 0, nl = 0, rslot = 0, mark = 0;
    uint32_t pending = 0;
    enum { RF = 1 << 7, FIRST = 1 << 11, PUB = 1 << 12 };

    void handoff_begin() { mark = nl; }
    void handoff_end() { for (int i = mark; i < nl; i++) P.loads[i] |= LD_HANDOFF; }
    void slot(uint32_t e, int s) { P.loads[nl++] = e | (s << 4); }
    void ring(uint32_t e) {
        slot(e | pending, rslot);
        pending = 0;
        rslot = (rslot + 1) % kRing;
    }
    static uint32_t tile(int isB, int b, int idx, int v) {
        return LD_VALID | (2 * isB + v) | (uint32_t)(b * 32 * 4096 + 64 * idx) << 10;
    }
    void pair(int isB, int b, int idx, uint32_t fk = 0, uint32_t fv = 0) {
        ring(tile(isB, b, idx, 0) | fk);
        ring(tile(isB, b, idx, 1) | fv);
    }
    void qproj(int mask, int layer, uint32_t f) {
        for (int p = 0; p < 3; p++) ring(LD_VALID | (4 + (layer & 1)) | (64 * p) << 10 | (p == 2 ? LD_HALF : 0u) | f);
        if (layer > 0) pending = LD_ANCHOR;
        P.prog[np++] = OP_QPROJ | (mask << 3) | (layer << 5);
        for (int b = 0; b < 2; b++)
            if ((mask >> b) & 1) P.merge[nm++] = MG_Q | (b << 2) | (layer << 3);
    }
    void oproj(int mask, int layer, uint32_t fLast) {
        for (int p = 0; p < 3; p++) ring(LD_VALID | (6 + (layer & 1)) | (16 * p) << 10 | (p == 2 ? fLast : 0u));
        P.prog[np++] = OP_OPROJ | (mask << 3) | (layer << 5);
    }
    void rfload(int from, int to, int isB, int b, int idx0) {
        for (int i = from; i < to; i++) ring(tile(isB, b, idx0 + i / 2, i & 1));
        P.prog[np++] = OP_RFLOAD | (from << 3) | (to << 6);
    }
    void seg(int b, int layer, uint32_t flags, const char* order) {
        uint64_t list = 0;
        for (int n = 0; order[n]; n++) {
            const char c = order[n];
            uint64_t item = 12;
            if (c >= 'a' && c <= 'c') item = 12 | (c - 'a' + 1);
            if (c >= 'A' && c <= 'C') item = 8 | (c - 'A' + 1);
            list |= item << (4 * n);
        }
        P.prog[np++] = OP_SEG | (b << 3) | ((layer & 1) << 4) | (flags & RF);
        P.prog[np++] = (uint32_t)list;
        P.prog[np++] = (uint32_t)(list >> 32);
        P.merge[nm++] = MG_ATTN | (b << 2) | (layer << 3) | ((flags & FIRST) ? 32 : 0) | ((flags & PUB) ? 64 : 0);
    }
};

void build_schedule(Params& P) {
    for (int i = 0; i < kMaxProg; i++) P.prog[i] = OP_END;
    for (int i = 0; i < kMaxMerge; i++) P.merge[i] = MG_END;
    for (int i = 0; i < kMaxLoads; i++) P.loads[i] = 0;
    const uint32_t anchorDelay[kAnchors] = {200, 200, 200, 200, 0};
    const uint32_t anchorCredit[kAnchors] = {kCredit, 2500, 2500, kCredit, 300};
    for (int i = 0; i < kAnchors; i++) {
        P.anchorDelay[i] = anchorDelay[i];
        P.anchorCredit[i] = anchorCredit[i];
    }

    Sched S{P};
    using F = Sched;
    const int keep[2] = {9, 10};
    auto kept = [&](int b, int idx, int v, uint32_t f) { return (2 * (15 - idx) + (1 - v)) < keep[b] ? f : 0u; };
    int nextD[2] = {3, 7}, nextH[2] = {11, 11}, nextK = 11;
    auto fill = [&](int b, int layer, int n, uint32_t flags = 0) {
        for (int i = 0; i < n; i++) S.pair(1, b, nextD[b]++);
        S.seg(b, layer, flags, &"dd"[2 - n]);
    };
    auto mixed = [&](int b, int layer, uint32_t flags, const char* order, int refill0, const int* pos) {
        int tiles = 0, done = 0, dst[6], n = 0;
        for (const char* c = order; *c; c++)
            if (*c >= 'a' && *c <= 'c') { dst[n++] = kRing + 2 * (*c - 'a'); dst[n++] = kRing + 2 * (*c - 'a') + 1; }
        for (const char* c = order; *c; c++) {
            if (*c != 'h' && *c != 'd' && *c != 'k') continue;
            const int idx = *c == 'h' ? nextH[b]++ : *c == 'k' ? nextK++ : nextD[b]++;
            for (int v = 0; v < 2; v++, tiles++) {
                for (; done < n && pos[done] <= tiles; done++) S.slot(F::tile(1, 1, refill0 + done / 2, done & 1) | LD_FAR, dst[done]);
                S.ring(F::tile(1, b, idx, v) | LD_FAR | kept(b, idx, v, *c == 'h' ? LD_HIT : *c == 'k' ? LD_KEEP : 0u));
            }
        }
        S.seg(b, layer, flags, order);
    };

    S.qproj(3, 0, LD_KEEP);
    S.slot(F::tile(0, 1, 0, 0), kRing);
    S.slot(F::tile(0, 1, 0, 1), kRing + 1);
    S.rfload(0, 8, 0, 0, 0);
    S.seg(0, 0, F::RF | F::FIRST | F::PUB, "");
    S.handoff_begin();
    for (int i = 1; i < 4; i++) S.pair(0, 1, i);
    S.seg(1, 0, F::FIRST | F::PUB, "addd");
    S.oproj(3, 0, LD_KEEP);
    for (int i = 0; i < 4; i++) S.slot(F::tile(1, 0, i / 2, i & 1), kRing + i);
    S.qproj(3, 1, LD_KEEP);
    for (int i = 4; i < 6; i++) S.slot(F::tile(1, 0, i / 2, i & 1), kRing + i);
    S.handoff_end();
    for (int i = 3; i < 16; i++) S.pair(1, 0, i, kept(0, i, 0, LD_KEEP), kept(0, i, 1, LD_KEEP));
    S.seg(0, 1, F::FIRST | F::PUB, "dddAdddBdddCdddd");
    S.handoff_begin();
    S.oproj(1, 1, 0);
    fill(1, 1, 2, F::FIRST);
    S.qproj(1, 2, LD_HIT);
    fill(1, 1, 1);
    S.seg(0, 2, F::RF | F::FIRST | F::PUB, "");
    S.rfload(0, 2, 1, 1, 3);
    S.oproj(1, 2, LD_HIT);
    S.rfload(2, 6, 1, 1, 3);
    fill(1, 1, 1);
    S.qproj(1, 3, LD_HIT);
    S.rfload(6, 8, 1, 1, 3);
    S.handoff_end();
    const int pos4[6] = {3, 3, 4, 5, 7, 7};
    mixed(0, 3, F::FIRST, "ahbhchhh", 0, pos4);
    mixed(1, 1, F::RF | F::PUB, "kkABkCkk", 0, nullptr);
    S.handoff_begin();
    S.oproj(2, 1, LD_KEEP);
    fill(0, 3, 2);
    S.qproj(2, 2, 0);
    fill(0, 3, 1);
    for (int i = 0; i < 4; i++) S.pair(0, 1, i);
    S.seg(1, 2, F::FIRST | F::PUB, "dddd");
    fill(0, 3, 1);
    S.oproj(2, 2, 0);
    fill(0, 3, 2);
    S.qproj(2, 3, 0);
    S.handoff_end();
    mixed(0, 3, F::PUB, "dd", 0, nullptr);
    const int pos6[6] = {3, 4, 7, 9, 10, 11};
    nextD[1] = 10;
    mixed(1, 3, F::RF | F::FIRST | F::PUB, "adbhchhAhBhC", 7, pos6);
    S.oproj(3, 3, LD_HIT);
}

typedef CUresult (*EncodeFn)(CUtensorMap*, CUtensorMapDataType, cuuint32_t, void*, const cuuint64_t*,
                             const cuuint64_t*, const cuuint32_t*, const cuuint32_t*, CUtensorMapInterleave,
                             CUtensorMapSwizzle, CUtensorMapL2promotion, CUtensorMapFloatOOBfill);

}

extern "C" void kernel_launch(void* const* d_in, const int* in_sizes, int n_in, void* d_out, int out_size) {
    (void)in_sizes; (void)n_in; (void)out_size;
    Params P;
    void* fn = nullptr;
    cudaDriverEntryPointQueryResult qr;
    cudaGetDriverEntryPoint("cuTensorMapEncodeTiled", &fn, cudaEnableDefault, &qr);
    EncodeFn encode = reinterpret_cast<EncodeFn>(fn);
    auto make_map = [&](int i, void* base, cuuint64_t rows, cuuint64_t rowBytes, cuuint64_t lines, cuuint32_t boxRows,
                        cuuint32_t boxLines) {
        const cuuint64_t dims[3] = {64, rows, lines};
        const cuuint64_t strides[2] = {rowBytes, 128};
        const cuuint32_t box[3] = {64, boxRows, boxLines};
        const cuuint32_t es[3] = {1, 1, 1};
        encode(&P.tm[i], CU_TENSOR_MAP_DATA_TYPE_BFLOAT16, 3, base, dims, strides, box, es, CU_TENSOR_MAP_INTERLEAVE_NONE,
               CU_TENSOR_MAP_SWIZZLE_128B, CU_TENSOR_MAP_L2_PROMOTION_NONE, CU_TENSOR_MAP_FLOAT_OOB_FILL_NONE);
    };
    for (int i = 0; i < 2; i++) {
        void* const* in = d_in + 5 * i;
        make_map(2 * i, in[1], 2 * 32 * 4096, 384, 3, 64, 3);
        make_map(2 * i + 1, in[2], 2 * 32 * 4096, 384, 3, 64, 3);
        make_map(4 + i, in[3], 640, 12288, 96, 64, 3);
        make_map(8 + i, in[3], 640, 12288, 96, 32, 3);
        make_map(6 + i, in[4], 6144, 1280, 10, 16, 10);
    }
    P.x = static_cast<const __nv_bfloat16*>(d_in[0]);
    P.out = static_cast<__nv_bfloat16*>(d_out);
    build_schedule(P);
    cudaFuncSetAttribute(fused_decode_kernel, cudaFuncAttributeMaxDynamicSharedMemorySize, kSmemBytes);
    fused_decode_kernel<<<kCtas, kThreads, kSmemBytes>>>(P);
}
```

```cpp
#include <cuda_runtime.h>
#include <cuda_bf16.h>
#include <cuda.h>
#include <stdint.h>

namespace {

constexpr int kCtas = 128;
constexpr int kThreads = 384;
constexpr int kSlotBytes = 3072;
constexpr int kRing = 3;
constexpr int kSlots = 9;
constexpr int kWRow = 192;

constexpr int kOffWbuf = kSlots * 8 * kSlotBytes;
constexpr int kOffMl = kOffWbuf + 8 * kWRow * 4;
constexpr int kOffCpart = kOffMl + 20 * 4;
constexpr int kOffQf = kOffCpart + 2 * kWRow * 4;
constexpr int kOffXn = kOffQf + 2 * 96 * 4;
constexpr int kOffObf = kOffXn + 2 * 160 * 2;
constexpr int kOffFull = kOffObf + 2 * 48 * 2;
constexpr int kOffEmpty = kOffFull + kSlots * 8;
constexpr int kOffSync = kOffEmpty + kSlots * 8;
constexpr int kOffAnchor = kOffSync + 14 * 8;
constexpr int kOffOwn = kOffAnchor + 8;
constexpr int kSmemBytes = kOffOwn + 32;
static_assert(kSmemBytes <= 232448, "shared memory budget");
constexpr int kBarRows = 0, kBarFree = 8, kBarQ = 16, kBarXn = 32, kBarO = 48;
constexpr int kBarSentQ = 64, kBarSentP = 80, kBarSentY = 96;

constexpr int kMaxProg = 72;
constexpr int kMaxMerge = 32;
constexpr int kMaxLoads = 176;
constexpr int kAnchors = 5;

constexpr uint32_t kTau = 970;
constexpr uint32_t kTauHandoff = 1000;
constexpr uint32_t kTauWo = 833;
constexpr uint32_t kCredit = 700;
constexpr uint32_t kWindow = 3;
constexpr uint32_t kStartWindow = 4, kStartLoads = 10, kStartDelay = 1000;
constexpr uint32_t kLook = 3, kLookFar = 4;
constexpr uint32_t kDelayX = 2200, kDelayP = 1000, kDelayIdle = 3500, kPauseX = 200;

enum : uint32_t { OP_END = 0, OP_QPROJ = 1, OP_RFLOAD = 2, OP_SEG = 3, OP_OPROJ = 4 };
enum : uint32_t { MG_END = 0, MG_ATTN = 1, MG_Q = 2 };
enum : uint32_t {
    LD_KEEP = 1u << 3,
    LD_HANDOFF = 1u << 8,
    LD_VALID = 1u << 9,
    LD_HALF = 1u << 28,
    LD_ANCHOR = 1u << 29,
    LD_FAR = 1u << 30,
    LD_HIT = 1u << 31
};

struct alignas(64) Params {
    CUtensorMap tm[10];
    const __nv_bfloat16* x;
    __nv_bfloat16* out;
    uint32_t anchorDelay[kAnchors], anchorCredit[kAnchors];
    uint32_t prog[kMaxProg];
    uint32_t merge[kMaxMerge];
    uint32_t loads[kMaxLoads];
};

__device__ uint4 g_q[2][32][4][40];
__device__ uint4 g_p[2][32][4][4][18];
constexpr int kAccPackets = 216;
constexpr float kAccDone = 129.f;
constexpr int kAccPad = 2;
__device__ float4 g_acc[2][3][kAccPackets * kAccPad];
constexpr int kOutReplicas = 8;
__device__ float4 g_out[2][kOutReplicas][kAccPackets * kAccPad];

constexpr uint32_t kSpinLimit = 1u << 22;

__device__ __forceinline__ void mbar_init(uint32_t bar, uint32_t count) {
    asm volatile("mbarrier.init.shared::cta.b64 [%0], %1;" ::"r"(bar), "r"(count) : "memory");
}
__device__ __forceinline__ void mbar_arrive(uint32_t bar) {
    asm volatile("mbarrier.arrive.shared::cta.b64 _, [%0];" ::"r"(bar) : "memory");
}
__device__ __forceinline__ bool mbar_test(uint32_t bar, uint32_t parity) {
    uint32_t ok;
    asm volatile(
        "{\n\t.reg .pred p;\n\t"
        "mbarrier.test_wait.parity.shared::cta.b64 p, [%1], %2;\n\t"
        "selp.u32 %0, 1, 0, p;\n\t}"
        : "=r"(ok) : "r"(bar), "r"(parity) : "memory");
    return __all_sync(0xffffffffu, ok);
}
__device__ __forceinline__ void mbar_expect(uint32_t bar, uint32_t bytes) {
    asm volatile("mbarrier.arrive.expect_tx.shared::cta.b64 _, [%0], %1;" ::"r"(bar), "r"(bytes) : "memory");
}
__device__ __forceinline__ void mbar_wait(uint32_t bar, uint32_t parity) {
    uint32_t ok, it = 0;
    do {
        asm volatile(
            "{\n\t.reg .pred p;\n\t"
            "mbarrier.try_wait.parity.shared::cta.b64 p, [%1], %2;\n\t"
            "selp.u32 %0, 1, 0, p;\n\t}"
            : "=r"(ok) : "r"(bar), "r"(parity) : "memory");
        if (++it > kSpinLimit) __trap();
    } while (!ok);
}
__device__ __forceinline__ bool mbar_try(uint32_t bar, uint32_t parity) {
    uint32_t ok;
    asm volatile(
        "{\n\t.reg .pred p;\n\t"
        "mbarrier.try_wait.parity.shared::cta.b64 p, [%1], %2;\n\t"
        "selp.u32 %0, 1, 0, p;\n\t}"
        : "=r"(ok) : "r"(bar), "r"(parity) : "memory");
    return __all_sync(0xffffffffu, ok);
}
__device__ __forceinline__ void mbar_wait_u(uint32_t bar, uint32_t parity) {
    for (uint32_t it = 0; !mbar_try(bar, parity); it++)
        if (it > kSpinLimit) __trap();
}
__device__ __forceinline__ void tma3d(uint32_t dst, const CUtensorMap* tm, int c0, int c1, int c2, uint32_t bar, uint64_t pol) {
    asm volatile(
        "cp.async.bulk.tensor.3d.shared::cluster.global.mbarrier::complete_tx::bytes.L2::cache_hint "
        "[%0], [%1, {%2, %3, %4}], [%5], %6;"
        ::"r"(dst), "l"(tm), "r"(c0), "r"(c1), "r"(c2), "r"(bar), "l"(pol) : "memory");
}
__device__ __forceinline__ void tma3d_prefetch(const CUtensorMap* tm, int c0, int c1, int c2, uint64_t pol) {
    asm volatile("cp.async.bulk.prefetch.tensor.3d.L2.global.L2::cache_hint [%0, {%1, %2, %3}], %4;"
                 ::"l"(tm), "r"(c0), "r"(c1), "r"(c2), "l"(pol) : "memory");
}
__device__ __forceinline__ uint64_t make_policy(bool keep) {
    uint64_t pol;
    if (keep) asm volatile("createpolicy.fractional.L2::evict_normal.b64 %0, 1.0;" : "=l"(pol));
    else      asm volatile("createpolicy.fractional.L2::evict_first.b64 %0, 1.0;" : "=l"(pol));
    return pol;
}
__device__ __forceinline__ void ldsm4(uint32_t (&r)[4], uint32_t addr) {
    asm volatile("ldmatrix.sync.aligned.m8n8.x4.shared.b16 {%0,%1,%2,%3}, [%4];"
                 : "=r"(r[0]), "=r"(r[1]), "=r"(r[2]), "=r"(r[3]) : "r"(addr) : "memory");
}
__device__ __forceinline__ void ldsm4t(uint32_t (&r)[4], uint32_t addr) {
    asm volatile("ldmatrix.sync.aligned.m8n8.x4.trans.shared.b16 {%0,%1,%2,%3}, [%4];"
                 : "=r"(r[0]), "=r"(r[1]), "=r"(r[2]), "=r"(r[3]) : "r"(addr) : "memory");
}
__device__ __forceinline__ void mma16816(float (&c)[4], const uint32_t (&a)[4], uint32_t b0, uint32_t b1) {
    asm volatile("mma.sync.aligned.m16n8k16.row.col.f32.bf16.bf16.f32 {%0,%1,%2,%3}, {%4,%5,%6,%7}, {%8,%9}, {%0,%1,%2,%3};"
                 : "+f"(c[0]), "+f"(c[1]), "+f"(c[2]), "+f"(c[3])
                 : "r"(a[0]), "r"(a[1]), "r"(a[2]), "r"(a[3]), "r"(b0), "r"(b1));
}
__device__ __forceinline__ float bf16r(float v) { return __bfloat162float(__float2bfloat16_rn(v)); }
__device__ __forceinline__ uint32_t pack_bf16(float lo, float hi) {
    uint32_t r;
    asm("cvt.rn.bf16x2.f32 %0, %1, %2;" : "=r"(r) : "f"(hi), "f"(lo));
    return r;
}
__device__ __forceinline__ bool elect() {
    uint32_t p;
    asm volatile("{\n\t.reg .pred e;\n\telect.sync _|e, 0xffffffff;\n\tselp.u32 %0, 1, 0, e;\n\t}" : "=r"(p));
    return p;
}
__device__ __forceinline__ float fast_sqrt(float v) {
    float r;
    asm("sqrt.approx.f32 %0, %1;" : "=f"(r) : "f"(v));
    return r;
}
__device__ __forceinline__ float ex2(float v) {
    float r;
    asm("ex2.approx.ftz.f32 %0, %1;" : "=f"(r) : "f"(v));
    return r;
}
__device__ __forceinline__ void st_packet(uint4* p, uint32_t a, uint32_t b, uint32_t c, uint32_t tag) {
    asm volatile(
        "{\n\t.reg .b64 lo, hi;\n\t.reg .b128 v;\n\t"
        "mov.b64 lo, {%1, %2};\n\tmov.b64 hi, {%3, %4};\n\tmov.b128 v, {lo, hi};\n\t"
        "st.relaxed.gpu.global.b128 [%0], v;\n\t}"
        ::"l"(p), "r"(a), "r"(b), "r"(c), "r"(tag) : "memory");
}
__device__ __forceinline__ void st_packet(uint4* p, float a, float b, float c, uint32_t tag) {
    st_packet(p, __float_as_uint(a), __float_as_uint(b), __float_as_uint(c), tag);
}
__device__ __forceinline__ uint4 ld_packet(const uint4* p) {
    uint4 v;
    asm volatile(
        "{\n\t.reg .b64 lo, hi;\n\t.reg .b128 v;\n\t"
        "ld.relaxed.gpu.global.b128 v, [%4];\n\t"
        "mov.b128 {lo, hi}, v;\n\tmov.b64 {%0, %1}, lo;\n\tmov.b64 {%2, %3}, hi;\n\t}"
        : "=r"(v.x), "=r"(v.y), "=r"(v.z), "=r"(v.w) : "l"(p) : "memory");
    return v;
}
__device__ __forceinline__ void red_packet(float4* p, float a, float b, float c) {
    asm volatile("red.relaxed.gpu.global.add.v4.f32 [%0], {%1, %2, %3, %4};"
                 ::"l"(p), "f"(a), "f"(b), "f"(c), "f"(1.f) : "memory");
}
#define POLL_UNTIL(pause, loads, done)            \
    for (uint32_t it_ = 0;; it_++) {              \
        loads;                                    \
        if (__all_sync(0xffffffffu, done)) break; \
        if (it_ > kSpinLimit) __trap();           \
        if (pause) __nanosleep(pause);            \
    }
__device__ __forceinline__ uint32_t round24(float v) {
    const uint32_t u = __float_as_uint(v);
    return u + ((u & 0x7f800000u) == 0x7f800000u ? 0u : 0x80u);
}
__device__ __forceinline__ void st_packet5(uint4* p, const float* v, uint32_t tag) {
    const uint32_t r0 = round24(v[0]), r1 = round24(v[1]), r2 = round24(v[2]), r3 = round24(v[3]), r4 = round24(v[4]);
    st_packet(p, __byte_perm(r0, r1, 0x5321), __byte_perm(r1, r2, 0x6532), __byte_perm(r2, r3, 0x7653),
              (r4 >> 8) | (tag << 24));
}
__device__ __forceinline__ void add_packet5(float (&a)[5], const uint4& v) {
    a[0] += __uint_as_float(v.x << 8);
    a[1] += __uint_as_float(__funnelshift_r(v.x, v.y, 16) & 0xffffff00u);
    a[2] += __uint_as_float(__funnelshift_r(v.y, v.z, 8) & 0xffffff00u);
    a[3] += __uint_as_float(v.z & 0xffffff00u);
    a[4] += __uint_as_float(v.w << 8);
}
__device__ __forceinline__ uint32_t now_ns() {
    uint32_t t;
    asm volatile("mov.u32 %0, %globaltimer_lo;" : "=r"(t));
    return t;
}
__device__ __forceinline__ int fresh_lane() {
    int lane = threadIdx.x & 31;
    asm volatile("" : "+r"(lane));
    return lane;
}
__device__ __forceinline__ void pause_ns(uint32_t ns) {
    const uint32_t t0 = now_ns();
    while (now_ns() - t0 < ns) __nanosleep(100);
}
__device__ __forceinline__ float bf_lo(uint32_t v) { return __uint_as_float(v << 16); }
__device__ __forceinline__ float bf_hi(uint32_t v) { return __uint_as_float(v & 0xffff0000u); }
__device__ __forceinline__ float warp_sum(float v) {
#pragma unroll
    for (int o = 16; o > 0; o >>= 1) v += __shfl_xor_sync(0xffffffffu, v, o);
    return v;
}

constexpr float kScale = 0.07216878364870322f * 1.4426950408889634f;

struct Attn {
    float m, l;
    float acc[3][4];
};

__device__ __forceinline__ uint32_t probability(Attn& st, float s) {
    const float e = ex2(s - st.m);
    st.l += e;
    const float hi = bf16r(e);
    const uint32_t hl = pack_bf16(hi, e - hi);
    uint32_t pv;
    asm volatile("movmatrix.sync.aligned.m8n8.trans.b16 %0, %1;" : "=r"(pv) : "r"(hl));
    return pv;
}

__device__ __forceinline__ uint32_t softmax_step(Attn& st, float s) {
    if (__any_sync(0xffffffffu, s > st.m)) {
        float mx = fmaxf(s, __shfl_xor_sync(0xffffffffu, s, 4));
        mx = fmaxf(mx, __shfl_xor_sync(0xffffffffu, mx, 8));
        mx = fmaxf(mx, __shfl_xor_sync(0xffffffffu, mx, 16));
        mx = fmaxf(mx, st.m);
        const float corr = ex2(st.m - mx);
        st.m = mx;
        st.l *= corr;
#pragma unroll
        for (int a = 0; a < 3; a++)
#pragma unroll
            for (int i = 0; i < 4; i++) st.acc[a][i] *= corr;
    }
    return probability(st, s);
}

__global__ void __launch_bounds__(kThreads, 1)
fused_decode_kernel(const __grid_constant__ Params P) {
    extern __shared__ __align__(1024) unsigned char smem[];
    const uint32_t sbase = (uint32_t)__cvta_generic_to_shared(smem);
    const uint32_t sync0 = sbase + kOffSync;
    float* const wbuf = reinterpret_cast<float*>(smem + kOffWbuf);

    const int lane = threadIdx.x & 31;
    const int w = __shfl_sync(0xffffffffu, threadIdx.x >> 5, 0);
    const int cta = blockIdx.x;
    const int h = cta >> 2, jq = cta & 3;

    if (w >= 10) {
        const int i0 = 80 * (w - 10) + lane;
#pragma unroll
        for (int i = 0; i < 3; i++)
            if (i < 2 || lane < 16)
                asm volatile("cp.async.cg.shared.global [%0], [%1], 16;"
                             ::"r"(sbase + kOffWbuf + 16 * (i0 + 32 * i)), "l"(reinterpret_cast<const uint4*>(P.x) + i0 + 32 * i) : "memory");
    }
    if (elect()) {
        if (w == 8) {
#pragma unroll
            for (int i = 0; i < kSlots; i++) {
                mbar_init(sbase + kOffFull + 8 * i, 1);
                mbar_init(sbase + kOffEmpty + 8 * i, 8);
            }
        } else if (w == 9) {
#pragma unroll
            for (int i = 0; i < 10; i++) asm volatile("prefetch.tensormap [%0];" ::"l"(&P.tm[i]) : "memory");
        } else if (w == 10) {
#pragma unroll
            for (int i = 0; i < 14; i++) mbar_init(sync0 + 8 * i, (8 * i == kBarRows || 8 * i >= kBarSentY) ? 8 : 1);
        }
        if (w != 9) asm volatile("fence.mbarrier_init.release.cluster;" ::: "memory");
    }
    __syncwarp();
    if (w == 8) {
        asm volatile("bar.arrive 1, %0;" ::"n"(kThreads) : "memory");
    } else {
        asm volatile("bar.sync 1, %0;" ::"n"(kThreads) : "memory");
    }

    if (w < 8) {
        asm volatile("setmaxnreg.inc.sync.aligned.u32 232;");
        const uint32_t full0 = sbase + kOffFull;
        const uint32_t frag0 = sbase + w * 1024 + (lane & 7) * 128 + (((lane >> 3) ^ (lane & 7)) << 4), frag1 = frag0 ^ 64;
        auto frag_addr = [&](uint32_t s, int k) { return ((k & 1) ? frag1 : frag0) + s * (8 * kSlotBytes) + (k >> 1) * 8192; };
        uint32_t par = 0, rpos = 0, nrows = 0;
        auto wait_tile = [&](uint32_t s) { mbar_wait(full0 + 8 * s, (par >> s) & 1u); };
        auto tile_ready = [&](uint32_t s) { return mbar_test(full0 + 8 * s, (par >> s) & 1u); };
        auto release = [&](uint32_t s) {
            par ^= 1u << s;
            __syncwarp();
            if (elect()) mbar_arrive(full0 + 8 * s + (kOffEmpty - kOffFull));
        };
        auto ring_release = [&]() {
            release(rpos);
            if (++rpos == kRing) rpos = 0;
        };
        auto row_acquire = [&]() { mbar_wait(sync0 + kBarFree, (nrows & 1) ^ 1); };
        auto row_publish = [&]() {
            __syncwarp();
            if (elect()) mbar_arrive(sync0 + kBarRows);
            nrows++;
        };

        uint32_t rf[8][6][4];
#pragma unroll
        for (int i = 0; i < 8; i++)
#pragma unroll
            for (int s = 0; s < 6; s++)
#pragma unroll
                for (int k = 0; k < 4; k++) rf[i][s][k] = 0;

#pragma unroll 1
        for (int pc = 0;; pc++) {
            const uint32_t op = P.prog[pc];
            const uint32_t kind = op & 7u;
            if (kind == OP_END) break;
            const int lane = fresh_lane();
            const int g = lane >> 2, t = lane & 3;
            float* const row = wbuf + w * kWRow;

            if (kind == OP_SEG) {
                const uint32_t b = (op >> 3) & 1u;
                mbar_wait(sync0 + kBarQ + 8 * b, (op >> 4) & 1u);
                const uint2* qf = reinterpret_cast<const uint2*>(smem + kOffQf) + b * 48 + (lane & 7);
                Attn st;
                st.m = -INFINITY; st.l = 0.f;
#pragma unroll
                for (int a = 0; a < 3; a++)
#pragma unroll
                    for (int i = 0; i < 4; i++) st.acc[a][i] = 0.f;

                if (op & (1u << 7)) {
                    float c[4][4] = {};
#pragma unroll
                    for (int k = 0; k < 6; k++) {
                        const uint2 q = qf[8 * k];
#pragma unroll
                        for (int i = 0; i < 4; i++) mma16816(c[i], rf[2 * i][k], q.x, q.y);
                    }
                    float sc[4];
#pragma unroll
                    for (int i = 0; i < 4; i++) sc[i] = (c[i][0] + c[i][3]) * kScale;
                    float mx = fmaxf(fmaxf(sc[0], sc[1]), fmaxf(sc[2], sc[3]));
                    mx = fmaxf(mx, __shfl_xor_sync(0xffffffffu, mx, 4));
                    mx = fmaxf(mx, __shfl_xor_sync(0xffffffffu, mx, 8));
                    st.m = fmaxf(mx, __shfl_xor_sync(0xffffffffu, mx, 16));
                    uint32_t pv[4];
#pragma unroll
                    for (int i = 0; i < 4; i++) pv[i] = probability(st, sc[i]);
#pragma unroll
                    for (int i = 0; i < 4; i++)
#pragma unroll
                        for (int k = 0; k < 6; k++)
                            mma16816(st.acc[k >> 1], rf[2 * i + 1][k], (g >> 1) == 2 * (k & 1) ? pv[i] : 0u,
                                     (g >> 1) == 2 * (k & 1) + 1 ? pv[i] : 0u);
                }

                uint32_t lo = P.prog[pc + 1], hi = P.prog[pc + 2];
                pc += 2;
                bool haveK = false;
#pragma unroll 1
                while (lo & 15u) {
                    const bool rel = lo & 4u;
                    uint32_t sK = kRing - 2 + 2 * (lo & 3u), sV = sK + 1;
                    if (!(lo & 3u)) {
                        sK = rpos;
                        sV = rpos == kRing - 1 ? 0 : rpos + 1;
                        rpos = sV == kRing - 1 ? 0 : sV + 1;
                    }
                    lo = __funnelshift_r(lo, hi, 4);
                    hi >>= 4;
                    if (!haveK) wait_tile(sK);
                    const bool haveV = tile_ready(sV);
                    float c[2][4] = {};
#pragma unroll
                    for (int k = 0; k < 6; k++) {
                        uint32_t a[4];
                        ldsm4(a, frag_addr(sK, k));
                        const uint2 q = qf[8 * k];
                        mma16816(c[k & 1], a, q.x, q.y);
                    }
                    if (rel) release(sK);
                    const uint32_t pv = softmax_step(st, ((c[0][0] + c[0][3]) + (c[1][0] + c[1][3])) * kScale);
                    if (!haveV) wait_tile(sV);
                    haveK = tile_ready((lo & 3u) ? kRing - 2 + 2 * (lo & 3u) : rpos);
#pragma unroll
                    for (int k = 0; k < 6; k++) {
                        uint32_t a[4];
                        ldsm4t(a, frag_addr(sV, k));
                        mma16816(st.acc[k >> 1], a, (g >> 1) == 2 * (k & 1) ? pv : 0u, (g >> 1) == 2 * (k & 1) + 1 ? pv : 0u);
                    }
                    if (rel) release(sV);
                }

                float l = st.l;
                l += __shfl_xor_sync(0xffffffffu, l, 4);
                l += __shfl_xor_sync(0xffffffffu, l, 8);
                l += __shfl_xor_sync(0xffffffffu, l, 16);
                row_acquire();
#pragma unroll
                for (int a = 0; a < 3; a++) {
                    row[64 * a + 16 * t + g] = st.acc[a][0] + st.acc[a][1];
                    row[64 * a + 16 * t + g + 8] = st.acc[a][2] + st.acc[a][3];
                }
                if (lane == 0) { wbuf[8 * kWRow + w] = st.m; wbuf[8 * kWRow + 8 + w] = l; }
                row_publish();
            } else if (kind == OP_RFLOAD) {
#pragma unroll 1
                for (uint32_t tile = (op >> 3) & 7u; tile < (op >> 6); tile++) {
                    wait_tile(rpos);
#pragma unroll
                    for (int i = 0; i < 8; i++) {
                        if (tile == i) {
#pragma unroll
                            for (int k = 0; k < 6; k++) {
                                if (i & 1) ldsm4t(rf[i][k], frag_addr(rpos, k));
                                else ldsm4(rf[i][k], frag_addr(rpos, k));
                            }
                        }
                    }
                    ring_release();
                }
            } else if (kind == OP_QPROJ) {
                const uint32_t mask = (op >> 3) & 3u;
#pragma unroll 1
                for (uint32_t b = 0; b < 2; b++)
                    if ((mask >> b) & 1u) mbar_wait(sync0 + kBarXn + 8 * b, (op >> 5) & 1u);
                const uint32_t bb = mask == 3u ? (g & 1) : (mask >> 1);
                const uint32_t* xs = reinterpret_cast<const uint32_t*>(smem + kOffXn) + bb * 80 + 4 * w + t;
                float acc[3][4] = {};
#pragma unroll 1
                for (int p = 0; p < 3; p++) {
                    wait_tile(rpos);
                    if (p < 2 || w < 4) {
                        const uint32_t xv = xs[32 * p];
                        const uint32_t shrink = p == 2 ? 4096 : 0;
#pragma unroll
                        for (int k = 0; k < 6; k++) {
                            uint32_t a[4];
                            ldsm4t(a, frag_addr(rpos, k) - (k >> 1) * shrink);
                            mma16816(acc[k >> 1], a, (g >> 1) == 2 * (k & 1) ? xv : 0u, (g >> 1) == 2 * (k & 1) + 1 ? xv : 0u);
                        }
                    }
                    ring_release();
                }
#pragma unroll 1
                for (uint32_t b = 0; b < 2; b++) {
                    if (!((mask >> b) & 1u)) continue;
                    row_acquire();
#pragma unroll
                    for (int a = 0; a < 3; a++) {
                        row[64 * a + 16 * t + g] = b ? acc[a][1] : acc[a][0];
                        row[64 * a + 16 * t + g + 8] = b ? acc[a][3] : acc[a][2];
                    }
                    row_publish();
                }
            } else {
                const uint32_t mask = (op >> 3) & 3u;
                const uint32_t bb = mask == 3u ? (g & 1) : (mask >> 1);
                const uint32_t* ob = reinterpret_cast<const uint32_t*>(smem + kOffObf) + bb * 24 + t;
                const uint32_t roff = ((lane & 7) + 8 * (lane >> 4)) * 128 + ((((lane >> 3) & 1) ^ (lane & 7)) << 4);
                uint32_t sl[3];
#pragma unroll
                for (int p = 0; p < 3; p++) {
                    sl[p] = rpos;
                    if (++rpos == kRing) rpos = 0;
                }
                auto frag = [&](uint32_t (&a)[4], int p, int mt) {
                    ldsm4t(a, ((sbase + sl[p] * 8 * kSlotBytes + roff) ^ (((5 * w + mt) & 3) << 5)) + ((5 * w + mt) >> 2) * 2048);
                };
                uint32_t a0[5][4];
                wait_tile(sl[0]);
#pragma unroll
                for (int mt = 0; mt < 5; mt++) frag(a0[mt], 0, mt);
                release(sl[0]);
                wait_tile(sl[1]);
                wait_tile(sl[2]);
                row_acquire();
                if (mask & 1u) mbar_wait(sync0 + kBarO, (op >> 5) & 1u);
                if (mask & 2u) mbar_wait(sync0 + kBarO + 8, (op >> 5) & 1u);
                float c[3][4] = {};
#pragma unroll
                for (int p = 0; p < 3; p++) {
                    const uint32_t b0 = ob[8 * p], b1 = ob[8 * p + 4];
#pragma unroll
                    for (int mt = 0; mt < 5; mt++) {
                        if (p > 0) frag(a0[mt], p, mt);
                        const bool on = (g >> 1) == (mt & 3);
                        mma16816(c[mt == 4 ? 2 : (mt & 1)], a0[mt], on ? b0 : 0u, on ? b1 : 0u);
                    }
                    if (p > 0) release(sl[p]);
                }
                row[16 * t + g] = c[0][0] + c[1][0]; row[80 + 16 * t + g] = c[0][1] + c[1][1];
                row[16 * t + g + 8] = c[0][2] + c[1][2]; row[80 + 16 * t + g + 8] = c[0][3] + c[1][3];
                if (t == 0) {
                    row[64 + g] = c[2][0]; row[144 + g] = c[2][1];
                    row[72 + g] = c[2][2]; row[152 + g] = c[2][3];
                }
                __syncwarp();
                if (lane < 27) {
                    const bool last = ((op >> 5) & 3u) == 3u;
                    float4* dst = (last ? g_out[0][cta % kOutReplicas] : g_acc[0][(op >> 5) & 3u]) + (27 * w + lane) * kAccPad;
                    const float* y = row + 3 * lane;
                    if (mask & 1u) red_packet(dst, y[0], y[1], lane < 26 ? y[2] : 0.f);
                    if (mask & 2u) red_packet(dst + (last ? kOutReplicas : 3) * kAccPad * kAccPackets, y[80], y[81], lane < 26 ? y[82] : 0.f);
                }
                __syncwarp();
                if (lane < 2 && ((mask >> lane) & 1u)) mbar_arrive(sync0 + kBarSentY + 8 * lane);
            }
        }
    } else {
        asm volatile("setmaxnreg.dec.sync.aligned.u32 40;");
        if (w == 8) {
            if (elect()) {
#pragma unroll
                for (int p = 0; p < kRing; p++) {
                    const CUtensorMap* tm = &P.tm[p == 2 ? 8 : 4];
                    mbar_expect(sbase + kOffFull + 8 * p, p == 2 ? 4 * kSlotBytes : 8 * kSlotBytes);
                    tma3d(sbase + p * 8 * kSlotBytes, tm, 0, 160 * jq + 64 * p, 3 * h, sbase + kOffFull + 8 * p, make_policy(false));
                    tma3d_prefetch(tm, 0, 160 * jq + 64 * p, 3 * h, make_policy(true));
                }
            }
            __syncwarp();
            const int rowA = h * 4096 + 3072 + 256 * jq, rowB = h * 4096 + 1024 * jq;
            const int rowWq = 160 * jq, rowWo = 192 * h + 48 * jq;
            const uint64_t polKeep = make_policy(true), polStream = make_policy(false);
            const uint32_t rot = 64u * 11u * ((h & 3) + ((h >> 2) & 3) + (h >> 4));
            auto coord = [&](uint32_t e) {
                const uint32_t off = (e >> 10) & 0x3ffffu;
                const uint32_t offB = (off & ~0x3ffu) + ((off + rot) & 0x3c0u) + rowB;
                return (int)((e & 4u) ? off + ((e & 2u) ? rowWo : rowWq) : ((e & 2u) ? offB : off + rowA));
            };
            auto line = [&](uint32_t e) { return (e & 6u) == 4u ? 3 * h : 0; };
            auto map = [&](uint32_t e) { return &P.tm[(e & 7u) + ((e >> 26) & 4u)]; };
            auto interval = [&](uint32_t e) {
                return (e & 6u) == 6u ? kTauWo : ((e & LD_HANDOFF) ? kTauHandoff : kTau) >> ((e >> 28) & 1u);
            };
            uint32_t par = 7u, recent = 0xf012u, latest = 2, m = 0, na = 0, credit = kCredit, next = now_ns() + kStartDelay;
            auto landed = [&](uint32_t s) { return mbar_test(sbase + kOffFull + 8 * s, ((par >> s) & 1u) ^ 1u); };
            uint32_t e = P.loads[kRing];
            int c1 = coord(e);
#pragma unroll 1
            for (uint32_t n = kRing; e & LD_VALID; n++) {
                const uint32_t s = (e >> 4) & 15u;
                const uint32_t full = sbase + kOffFull + 8 * s;
                const uint32_t enext = P.loads[n + 1];
                if (m < n) m = n;
                for (uint32_t it = 0; !mbar_test(full + (kOffEmpty - kOffFull), ((par >> s) & 1u) ^ 1u); it++) {
                    if (it > 16 * kSpinLimit) __trap();
                    const uint32_t f = P.loads[m];
                    if (m >= n + ((e & LD_FAR) ? kLookFar : kLook) || !(f & LD_VALID)) continue;
                    if (f & LD_HIT) { m++; continue; }
                    const uint32_t now = now_ns();
                    if ((int)(now - next) >= 0 && landed(latest)) {
                        if (elect()) tma3d_prefetch(map(f), 0, coord(f), line(f), polStream);
                        next = now + interval(f);
                        m++;
                    }
                }
                if (e & LD_ANCHOR) {
                    const uint32_t t0 = __shfl_sync(0xffffffffu, *reinterpret_cast<volatile uint32_t*>(smem + kOffAnchor), 0) + P.anchorDelay[na];
                    if (m <= n || (int)(t0 - next) > 0) next = t0;
                    credit = P.anchorCredit[na++];
                }
                const bool fromHbm = !(e & LD_HIT) && m <= n;
                if (fromHbm) {
                    const uint32_t o = (recent >> (4 * (n < kStartLoads ? kStartWindow : kWindow) - 4)) & 15u;
                    if (o != s && o != 15u) mbar_wait_u(sbase + kOffFull + 8 * o, ((par >> o) & 1u) ^ 1u);
                    uint32_t now = now_ns();
                    while ((int)(now - next) < 0) now = now_ns();
                    if ((int)(now - credit - next) > 0) next = now - credit;
                    next += interval(e);
                }
                if (elect()) {
                    mbar_expect(full, (e & 6u) == 6u ? 20480 : (8 * kSlotBytes) >> ((e >> 28) & 1u));
                    tma3d(sbase + s * 8 * kSlotBytes, map(e), 0, c1, line(e), full, polStream);
                    if (e & LD_KEEP) tma3d_prefetch(map(e), 0, c1, line(e), polKeep);
                }
                const uint32_t x = recent ^ (s * 0x1111u);
                recent |= (~(((x & 0x7777u) + 0x7777u) | x) & 0x8888u) * 15u >> 3;
                if (fromHbm) {
                    recent = (recent << 4) | s;
                    latest = s;
                }
                par ^= 1u << s;
                e = enext;
                c1 = coord(e);
            }
        } else {
            if (w == 9) {
#pragma unroll 1
                for (int n = 0;; n++) {
                    const uint32_t job = P.merge[n];
                    if ((job & 3u) == MG_END) break;
                    const uint32_t b = (job >> 2) & 1u;
                    const uint32_t tag = 1 + ((job >> 3) & 3u);
                    mbar_wait(sync0 + kBarRows, n & 1);
                    if ((job & 3u) == MG_Q) {
                        float o[5] = {}, e[5] = {};
                        const float* ext = wbuf + 2 * (lane & 3) * kWRow + 5 * min(32 + (lane >> 2), 38);
#pragma unroll
                        for (int k = 0; k < 5; k++) e[k] = ext[k] + ext[kWRow + k];
#pragma unroll
                        for (int i = 0; i < 8; i++)
#pragma unroll
                            for (int k = 0; k < 5; k++) o[k] += wbuf[i * kWRow + 5 * lane + k];
                        st_packet5(&g_q[b][h][jq][lane], o, tag);
#pragma unroll
                        for (int k = 0; k < 5; k++) {
                            e[k] += __shfl_xor_sync(0xffffffffu, e[k], 1);
                            e[k] += __shfl_xor_sync(0xffffffffu, e[k], 2);
                        }
                        if ((lane & 3) == 0) st_packet5(&g_q[b][h][jq][32 + (lane >> 2)], e, tag);
                        __syncwarp();
                        if (lane == 0) mbar_arrive(sync0 + kBarSentQ + 8 * b);
                    } else {
                        float2* cp = reinterpret_cast<float2*>(smem + kOffCpart) + b * (kWRow / 2) + 3 * lane;
                        float2* cml = reinterpret_cast<float2*>(smem + kOffMl + 64) + b;
                        const float4* ml = reinterpret_cast<const float4*>(smem + kOffMl);
                        const bool merge = !(job & 32u);
                        const float2 pml = merge ? *cml : make_float2(-INFINITY, 0.f);
                        const float4 m0 = ml[0], m1 = ml[1];
                        float sc[8] = {m0.x, m0.y, m0.z, m0.w, m1.x, m1.y, m1.z, m1.w};
                        const float M = fmaxf(fmaxf(fmaxf(fmaxf(sc[0], sc[1]), fmaxf(sc[2], sc[3])),
                                                    fmaxf(fmaxf(sc[4], sc[5]), fmaxf(sc[6], sc[7]))), pml.x);
#pragma unroll
                        for (int i = 0; i < 8; i++) sc[i] = ex2(sc[i] - M);
                        const float ps = ex2(pml.x - M);
                        float2 o[3];
#pragma unroll
                        for (int k = 0; k < 3; k++) {
                            o[k] = merge ? cp[k] : make_float2(0.f, 0.f);
                            o[k].x *= ps; o[k].y *= ps;
                        }
#pragma unroll
                        for (int i = 0; i < 8; i++)
#pragma unroll
                            for (int k = 0; k < 3; k++) {
                                const float2 v = reinterpret_cast<const float2*>(wbuf)[i * (kWRow / 2) + 3 * lane + k];
                                o[k].x = fmaf(v.x, sc[i], o[k].x);
                                o[k].y = fmaf(v.y, sc[i], o[k].y);
                            }
                        const float4 l0 = ml[2], l1 = ml[3];
                        const float L = fmaf(pml.y, ps, ((l0.x * sc[0] + l0.y * sc[1]) + (l0.z * sc[2] + l0.w * sc[3])) +
                                                        ((l1.x * sc[4] + l1.y * sc[5]) + (l1.z * sc[6] + l1.w * sc[7])));
                        if (job & 64u) {
                            uint4* dst = &g_p[b][h][lane >> 3][jq][2 * (lane & 7)];
                            st_packet(dst, o[0].x, o[0].y, o[1].x, tag);
                            st_packet(dst + 1, o[1].y, o[2].x, o[2].y, tag);
                            if (lane < 8) st_packet(&g_p[b][h][lane >> 1][jq][16 + (lane & 1)], M, L, 0.f, tag);
                            if (lane == 0) mbar_arrive(sync0 + kBarSentP + 8 * b);
                        } else {
#pragma unroll
                            for (int k = 0; k < 3; k++) cp[k] = o[k];
                            __syncwarp();
                            if (lane == 0) *cml = make_float2(M, L);
                        }
                    }
                    __syncwarp();
                    if (lane == 0) mbar_arrive(sync0 + kBarFree);
                }
            } else {
                const uint32_t b = w - 10;
                __nv_bfloat16* const xn = reinterpret_cast<__nv_bfloat16*>(smem + kOffXn) + b * 160;
                __nv_bfloat16* const qd = reinterpret_cast<__nv_bfloat16*>(smem + kOffQf) + b * 192;
                __nv_bfloat16* const ob = reinterpret_cast<__nv_bfloat16*>(smem + kOffObf) + b * 48;
                uint2* const own = reinterpret_cast<uint2*>(smem + kOffOwn) + 2 * b;
#pragma unroll 1
                for (uint32_t layer = 0; layer < 4; layer++) {
                    const uint32_t tag = layer + 1;
                    {
                        int lane = fresh_lane();
                        uint32_t x01[7], x2[7];
                        if (layer == 0) {
                            const uint4* stage = reinterpret_cast<const uint4*>(wbuf) + 80 * b;
                            asm volatile("cp.async.wait_all;" ::: "memory");
                            __syncwarp();
#pragma unroll
                            for (int i = 0; i < 7; i++) {
                                const int p = lane + 32 * i, u = p % 27;
                                const unsigned short* xp = reinterpret_cast<const unsigned short*>(stage) + (p / 27) * 80 + 3 * u;
                                x01[i] = p < kAccPackets ? xp[0] | ((uint32_t)xp[1] << 16) : 0u;
                                x2[i] = (p < kAccPackets && u < 26) ? xp[2] : 0u;
                            }
                        } else {
                            mbar_wait(sync0 + kBarSentY + 8 * b, (layer - 1) & 1);
                            pause_ns(kDelayX);
                            uint4 v[7];
                            const uint4* src = reinterpret_cast<const uint4*>(&g_acc[b][layer - 1][lane * kAccPad]);
                            const uint32_t done = __float_as_uint(kAccDone);
                            POLL_UNTIL(kPauseX, v[0] = ld_packet(src + (27 * (cta & 7) + min(lane, 26) - lane) * kAccPad), v[0].w == done);
                            POLL_UNTIL(kPauseX,
                                v[0] = ld_packet(src); v[1] = ld_packet(src + 32 * kAccPad); v[2] = ld_packet(src + 64 * kAccPad);
                                v[3] = ld_packet(src + 96 * kAccPad); v[4] = ld_packet(src + 128 * kAccPad);
                                v[5] = ld_packet(src + 160 * kAccPad); v[6] = ld_packet(src + (lane < 24 ? 192 * kAccPad : 0)),
                                v[0].w == done && v[1].w == done && v[2].w == done && v[3].w == done && v[4].w == done &&
                                    v[5].w == done && v[6].w == done);
#pragma unroll
                            for (int i = 0; i < 7; i++) {
                                x01[i] = pack_bf16(__uint_as_float(v[i].x), __uint_as_float(v[i].y));
                                x2[i] = pack_bf16(__uint_as_float(v[i].z), 0.f);
                            }
                            if (lane >= 24) x01[6] = x2[6] = 0u;
                        }
#pragma unroll
                        for (int i = 0; i < 7; i++) {
                            const int p = lane + 32 * i;
                            if ((p & 127) == cta && p < kAccPackets) {
                                own[i >> 2] = make_uint2(x01[i], x2[i]);
                            }
                        }
                        float sum = 0.f;
#pragma unroll
                        for (int i = 0; i < 7; i++) sum += (bf_lo(x01[i]) + bf_hi(x01[i])) + bf_lo(x2[i]);
                        const float mean = warp_sum(sum) * (1.f / 640.f);
                        float sq = 0.f;
#pragma unroll
                        for (int i = 0; i < 7; i++) {
                            const bool none = i == 6 && lane >= 24;
                            const float d0 = none ? 0.f : bf_lo(x01[i]) - mean, d1 = none ? 0.f : bf_hi(x01[i]) - mean;
                            const bool last = lane == 26 - 5 * i || lane == 53 - 5 * i;
                            const float d2 = (none || last) ? 0.f : bf_lo(x2[i]) - mean;
                            sq += fmaf(d0, d0, fmaf(d1, d1, d2 * d2));
                        }
                        const float var = warp_sum(sq) * (1.f / 640.f);
                        const float meanb = bf16r(mean);
                        const float rden = __fdividef(1.f, bf16r(fast_sqrt(bf16r(bf16r(var) + 1e-5f))));
#pragma unroll
                        for (int i = 0; i < 7; i++) {
                            const uint32_t q = lane + 32 * i - 54 * jq;
                            if (q < 54u) {
                                const int c = 3 * q - (q >= 27u);
                                xn[c] = __float2bfloat16_rn(bf16r(bf_lo(x01[i]) - meanb) * rden);
                                xn[c + 1] = __float2bfloat16_rn(bf16r(bf_hi(x01[i]) - meanb) * rden);
                                if (q != 26u && q != 53u) xn[c + 2] = __float2bfloat16_rn(bf16r(bf_lo(x2[i]) - meanb) * rden);
                            }
                        }
                        if (lane == 0) *reinterpret_cast<volatile uint32_t*>(smem + kOffAnchor) = now_ns();
                        __syncwarp();
                        if (lane == 0) mbar_arrive(sync0 + kBarXn + 8 * b);
                        if (layer >= 2 && lane < 4 && cta + 128 * (lane >> 1) < kAccPackets)
                            g_acc[b][layer - 2][(cta + 128 * (lane >> 1)) * kAccPad + (lane & 1)] = make_float4(0.f, 0.f, 0.f, 0.f);
                        __syncwarp();
                    }
                    {
                        const int lane = fresh_lane();
                        mbar_wait(sync0 + kBarSentQ + 8 * b, layer & 1);
                        if (layer == 0 || (layer == 1 && b == 1)) pause_ns(kDelayIdle);
                        uint4 v[5];
                        const uint4* src = &g_q[b][h][0][lane];
                        const uint4* ext = &g_q[b][h][lane & 3][lane < 28 ? 32 + (lane >> 2) : 38];
                        POLL_UNTIL(0,
                            v[0] = ld_packet(src); v[1] = ld_packet(src + 40); v[2] = ld_packet(src + 80);
                            v[3] = ld_packet(src + 120); v[4] = ld_packet(ext),
                            (v[0].w >> 24) == tag && (v[1].w >> 24) == tag && (v[2].w >> 24) == tag &&
                                (v[3].w >> 24) == tag && (v[4].w >> 24) == tag);
                        __syncwarp();
                        auto store_q = [&](int d, float q) {
                            qd[(d & ~31) + ((d >> 3) & 1) * 16 + ((d >> 1) & 3) * 4 + ((d >> 4) & 1) * 2 + (d & 1)] =
                                __float2bfloat16_rn(q);
                        };
                        float a[5] = {};
#pragma unroll
                        for (int i = 0; i < 4; i++) add_packet5(a, v[i]);
#pragma unroll
                        for (int k = 0; k < 5; k++) store_q(5 * lane + k, a[k]);
                        float e[5] = {};
                        add_packet5(e, v[4]);
#pragma unroll
                        for (int k = 0; k < 5; k++) {
                            e[k] += __shfl_xor_sync(0xffffffffu, e[k], 1);
                            e[k] += __shfl_xor_sync(0xffffffffu, e[k], 2);
                            const int d = 160 + 5 * (lane >> 2) + k;
                            if ((lane & 3) == 0 && d < 192) store_q(d, e[k]);
                        }
                        __syncwarp();
                        if (lane == 0) mbar_arrive(sync0 + kBarQ + 8 * b);
                    }
                    {
                        const int lane = fresh_lane();
                        mbar_wait(sync0 + kBarSentP + 8 * b, layer & 1);
                        pause_ns((b == 0 && (layer == 0 || layer == 3)) ? kDelayIdle : (layer == 3 ? 0 : kDelayP));
                        uint4 v0, v1, ml;
                        const uint4* src = &g_p[b][h][jq][2 * (lane >> 4)][lane & 15];
                        const uint4* mls = &g_p[b][h][jq][lane & 3][16];
                        POLL_UNTIL(0, v0 = ld_packet(src); v1 = ld_packet(src + 18); ml = ld_packet(mls),
                                   v0.w == tag && v1.w == tag && ml.w == tag);
                        __syncwarp();
                        const float mi = __uint_as_float(ml.x);
                        float M = fmaxf(mi, __shfl_xor_sync(0xffffffffu, mi, 1));
                        M = fmaxf(M, __shfl_xor_sync(0xffffffffu, M, 2));
                        const float sc = ex2(mi - M);
                        float L = __uint_as_float(ml.y) * sc;
                        L += __shfl_xor_sync(0xffffffffu, L, 1);
                        L += __shfl_xor_sync(0xffffffffu, L, 2);
                        const float s0 = __shfl_sync(0xffffffffu, sc, 2 * (lane >> 4));
                        const float s1 = __shfl_sync(0xffffffffu, sc, 2 * (lane >> 4) + 1);
                        float o0 = fmaf(__uint_as_float(v0.x), s0, __uint_as_float(v1.x) * s1);
                        float o1 = fmaf(__uint_as_float(v0.y), s0, __uint_as_float(v1.y) * s1);
                        float o2 = fmaf(__uint_as_float(v0.z), s0, __uint_as_float(v1.z) * s1);
                        o0 += __shfl_xor_sync(0xffffffffu, o0, 16);
                        o1 += __shfl_xor_sync(0xffffffffu, o1, 16);
                        o2 += __shfl_xor_sync(0xffffffffu, o2, 16);
                        if (lane < 16) {
                            ob[3 * lane] = __float2bfloat16_rn(__fdividef(o0, L));
                            ob[3 * lane + 1] = __float2bfloat16_rn(__fdividef(o1, L));
                            ob[3 * lane + 2] = __float2bfloat16_rn(__fdividef(o2, L));
                        }
                        __syncwarp();
                        if (lane == 0) mbar_arrive(sync0 + kBarO + 8 * b);
                        const int p = cta + 128 * lane;
                        if (p < kAccPackets) {
                            const uint2 v = own[lane];
                            red_packet((layer == 3 ? g_out[b][0] : g_acc[b][layer]) + p * kAccPad, bf_lo(v.x), bf_hi(v.x), bf_lo(v.y));
                        }
                    }
                }
                {
                    mbar_wait(sync0 + kBarSentY + 8 * b, 1);
                    const int p = cta + 128 * ((lane / kOutReplicas) & 1), r = lane % kOutReplicas;
                    float4* src = &g_out[b][r][(p < kAccPackets ? p : cta) * kAccPad];
                    const float want = kCtas / kOutReplicas + (r == 0);
                    uint4 v;
                    for (uint32_t it = 0;; it++) {
                        v = ld_packet(reinterpret_cast<const uint4*>(src));
                        if (__all_sync(0xffffffffu, v.w == __float_as_uint(want))) break;
                        if (it > kSpinLimit) __trap();
                    }
                    float o0 = __uint_as_float(v.x), o1 = __uint_as_float(v.y), o2 = __uint_as_float(v.z);
#pragma unroll
                    for (int o = 1; o < kOutReplicas; o <<= 1) {
                        o0 += __shfl_xor_sync(0xffffffffu, o0, o);
                        o1 += __shfl_xor_sync(0xffffffffu, o1, o);
                        o2 += __shfl_xor_sync(0xffffffffu, o2, o);
                    }
                    if (lane < 2 * kOutReplicas && p < kAccPackets) {
                        if (r < 3 - (p % 27 == 26))
                            P.out[b * 640 + (p / 27) * 80 + 3 * (p % 27) + r] = __float2bfloat16_rn(r == 0 ? o0 : r == 1 ? o1 : o2);
                        *src = make_float4(0.f, 0.f, 0.f, 0.f);
                        if (r == 0) g_acc[b][2][p * kAccPad] = make_float4(0.f, 0.f, 0.f, 0.f);
                    }
                }
            }
        }
    }
}


struct Sched {
    Params& P;
    int np = 0, nm = 0, nl = 0, rslot = 0, mark = 0;
    uint32_t pending = 0;
    enum { RF = 1 << 7, FIRST = 1 << 11, PUB = 1 << 12 };

    void handoff_begin() { mark = nl; }
    void handoff_end() { for (int i = mark; i < nl; i++) P.loads[i] |= LD_HANDOFF; }
    void slot(uint32_t e, int s) { P.loads[nl++] = e | (s << 4); }
    void ring(uint32_t e) {
        slot(e | pending, rslot);
        pending = 0;
        rslot = (rslot + 1) % kRing;
    }
    static uint32_t tile(int isB, int b, int idx, int v) {
        return LD_VALID | (2 * isB + v) | (uint32_t)(b * 32 * 4096 + 64 * idx) << 10;
    }
    void pair(int isB, int b, int idx, uint32_t fk = 0, uint32_t fv = 0) {
        ring(tile(isB, b, idx, 0) | fk);
        ring(tile(isB, b, idx, 1) | fv);
    }
    void qproj(int mask, int layer, uint32_t f) {
        for (int p = 0; p < 3; p++) ring(LD_VALID | (4 + (layer & 1)) | (64 * p) << 10 | (p == 2 ? LD_HALF : 0u) | f);
        if (layer > 0) pending = LD_ANCHOR;
        P.prog[np++] = OP_QPROJ | (mask << 3) | (layer << 5);
        for (int b = 0; b < 2; b++)
            if ((mask >> b) & 1) P.merge[nm++] = MG_Q | (b << 2) | (layer << 3);
    }
    void oproj(int mask, int layer, uint32_t fLast) {
        for (int p = 0; p < 3; p++) ring(LD_VALID | (6 + (layer & 1)) | (16 * p) << 10 | (p == 2 ? fLast : 0u));
        P.prog[np++] = OP_OPROJ | (mask << 3) | (layer << 5);
    }
    void rfload(int from, int to, int isB, int b, int idx0) {
        for (int i = from; i < to; i++) ring(tile(isB, b, idx0 + i / 2, i & 1));
        P.prog[np++] = OP_RFLOAD | (from << 3) | (to << 6);
    }
    void seg(int b, int layer, uint32_t flags, const char* order) {
        uint64_t list = 0;
        for (int n = 0; order[n]; n++) {
            const char c = order[n];
            uint64_t item = 12;
            if (c >= 'a' && c <= 'c') item = 12 | (c - 'a' + 1);
            if (c >= 'A' && c <= 'C') item = 8 | (c - 'A' + 1);
            list |= item << (4 * n);
        }
        P.prog[np++] = OP_SEG | (b << 3) | ((layer & 1) << 4) | (flags & RF);
        P.prog[np++] = (uint32_t)list;
        P.prog[np++] = (uint32_t)(list >> 32);
        P.merge[nm++] = MG_ATTN | (b << 2) | (layer << 3) | ((flags & FIRST) ? 32 : 0) | ((flags & PUB) ? 64 : 0);
    }
};

void build_schedule(Params& P) {
    for (int i = 0; i < kMaxProg; i++) P.prog[i] = OP_END;
    for (int i = 0; i < kMaxMerge; i++) P.merge[i] = MG_END;
    for (int i = 0; i < kMaxLoads; i++) P.loads[i] = 0;
    const uint32_t anchorDelay[kAnchors] = {200, 200, 200, 200, 0};
    const uint32_t anchorCredit[kAnchors] = {kCredit, 2500, 2500, kCredit, 300};
    for (int i = 0; i < kAnchors; i++) {
        P.anchorDelay[i] = anchorDelay[i];
        P.anchorCredit[i] = anchorCredit[i];
    }

    Sched S{P};
    using F = Sched;
    const int keep[2] = {9, 10};
    auto kept = [&](int b, int idx, int v, uint32_t f) { return (2 * (15 - idx) + (1 - v)) < keep[b] ? f : 0u; };
    int nextD[2] = {3, 7}, nextH[2] = {11, 11}, nextK = 11;
    auto fill = [&](int b, int layer, int n, uint32_t flags = 0) {
        for (int i = 0; i < n; i++) S.pair(1, b, nextD[b]++);
        S.seg(b, layer, flags, &"dd"[2 - n]);
    };
    auto mixed = [&](int b, int layer, uint32_t flags, const char* order, int refill0, const int* pos) {
        int tiles = 0, done = 0, dst[6], n = 0;
        for (const char* c = order; *c; c++)
            if (*c >= 'a' && *c <= 'c') { dst[n++] = kRing + 2 * (*c - 'a'); dst[n++] = kRing + 2 * (*c - 'a') + 1; }
        for (const char* c = order; *c; c++) {
            if (*c != 'h' && *c != 'd' && *c != 'k') continue;
            const int idx = *c == 'h' ? nextH[b]++ : *c == 'k' ? nextK++ : nextD[b]++;
            for (int v = 0; v < 2; v++, tiles++) {
                for (; done < n && pos[done] <= tiles; done++) S.slot(F::tile(1, 1, refill0 + done / 2, done & 1) | LD_FAR, dst[done]);
                S.ring(F::tile(1, b, idx, v) | LD_FAR | kept(b, idx, v, *c == 'h' ? LD_HIT : *c == 'k' ? LD_KEEP : 0u));
            }
        }
        S.seg(b, layer, flags, order);
    };

    S.qproj(3, 0, LD_KEEP);
    S.slot(F::tile(0, 1, 0, 0), kRing);
    S.slot(F::tile(0, 1, 0, 1), kRing + 1);
    S.rfload(0, 8, 0, 0, 0);
    S.seg(0, 0, F::RF | F::FIRST | F::PUB, "");
    S.handoff_begin();
    for (int i = 1; i < 4; i++) S.pair(0, 1, i);
    S.seg(1, 0, F::FIRST | F::PUB, "addd");
    S.oproj(3, 0, LD_KEEP);
    for (int i = 0; i < 4; i++) S.slot(F::tile(1, 0, i / 2, i & 1), kRing + i);
    S.qproj(3, 1, LD_KEEP);
    for (int i = 4; i < 6; i++) S.slot(F::tile(1, 0, i / 2, i & 1), kRing + i);
    S.handoff_end();
    for (int i = 3; i < 16; i++) S.pair(1, 0, i, kept(0, i, 0, LD_KEEP), kept(0, i, 1, LD_KEEP));
    S.seg(0, 1, F::FIRST | F::PUB, "dddAdddBdddCdddd");
    S.handoff_begin();
    S.oproj(1, 1, 0);
    fill(1, 1, 2, F::FIRST);
    S.qproj(1, 2, LD_HIT);
    fill(1, 1, 1);
    S.seg(0, 2, F::RF | F::FIRST | F::PUB, "");
    S.rfload(0, 2, 1, 1, 3);
    S.oproj(1, 2, LD_HIT);
    S.rfload(2, 6, 1, 1, 3);
    fill(1, 1, 1);
    S.qproj(1, 3, LD_HIT);
    S.rfload(6, 8, 1, 1, 3);
    S.handoff_end();
    const int pos4[6] = {3, 3, 4, 5, 7, 7};
    mixed(0, 3, F::FIRST, "ahbhchhh", 0, pos4);
    mixed(1, 1, F::RF | F::PUB, "kkABkCkk", 0, nullptr);
    S.handoff_begin();
    S.oproj(2, 1, LD_KEEP);
    fill(0, 3, 2);
    S.qproj(2, 2, 0);
    fill(0, 3, 1);
    for (int i = 0; i < 4; i++) S.pair(0, 1, i);
    S.seg(1, 2, F::FIRST | F::PUB, "dddd");
    fill(0, 3, 1);
    S.oproj(2, 2, 0);
    fill(0, 3, 2);
    S.qproj(2, 3, 0);
    S.handoff_end();
    mixed(0, 3, F::PUB, "dd", 0, nullptr);
    const int pos6[6] = {3, 4, 7, 9, 10, 11};
    nextD[1] = 10;
    mixed(1, 3, F::RF | F::FIRST | F::PUB, "adbhchhAhBhC", 7, pos6);
    S.oproj(3, 3, LD_HIT);
}

typedef CUresult (*EncodeFn)(CUtensorMap*, CUtensorMapDataType, cuuint32_t, void*, const cuuint64_t*,
                             const cuuint64_t*, const cuuint32_t*, const cuuint32_t*, CUtensorMapInterleave,
                             CUtensorMapSwizzle, CUtensorMapL2promotion, CUtensorMapFloatOOBfill);

}

extern "C" void kernel_launch(void* const* d_in, const int* in_sizes, int n_in, void* d_out, int out_size) {
    (void)in_sizes; (void)n_in; (void)out_size;
    Params P;
    void* fn = nullptr;
    cudaDriverEntryPointQueryResult qr;
    cudaGetDriverEntryPoint("cuTensorMapEncodeTiled", &fn, cudaEnableDefault, &qr);
    EncodeFn encode = reinterpret_cast<EncodeFn>(fn);
    auto make_map = [&](int i, void* base, cuuint64_t rows, cuuint64_t rowBytes, cuuint64_t lines, cuuint32_t boxRows,
                        cuuint32_t boxLines) {
        const cuuint64_t dims[3] = {64, rows, lines};
        const cuuint64_t strides[2] = {rowBytes, 128};
        const cuuint32_t box[3] = {64, boxRows, boxLines};
        const cuuint32_t es[3] = {1, 1, 1};
        encode(&P.tm[i], CU_TENSOR_MAP_DATA_TYPE_BFLOAT16, 3, base, dims, strides, box, es, CU_TENSOR_MAP_INTERLEAVE_NONE,
               CU_TENSOR_MAP_SWIZZLE_128B, CU_TENSOR_MAP_L2_PROMOTION_NONE, CU_TENSOR_MAP_FLOAT_OOB_FILL_NONE);
    };
    for (int i = 0; i < 2; i++) {
        void* const* in = d_in + 5 * i;
        make_map(2 * i, in[1], 2 * 32 * 4096, 384, 3, 64, 3);
        make_map(2 * i + 1, in[2], 2 * 32 * 4096, 384, 3, 64, 3);
        make_map(4 + i, in[3], 640, 12288, 96, 64, 3);
        make_map(8 + i, in[3], 640, 12288, 96, 32, 3);
        make_map(6 + i, in[4], 6144, 1280, 10, 16, 10);
    }
    P.x = static_cast<const __nv_bfloat16*>(d_in[0]);
    P.out = static_cast<__nv_bfloat16*>(d_out);
    build_schedule(P);
    cudaFuncSetAttribute(fused_decode_kernel, cudaFuncAttributeMaxDynamicSharedMemorySize, kSmemBytes);
    fused_decode_kernel<<<kCtas, kThreads, kSmemBytes>>>(P);
}
```

```cpp
#include <cuda_runtime.h>
#include <cuda_bf16.h>
#include <cuda.h>
#include <stdint.h>

namespace {

constexpr int kCtas = 128;
constexpr int kThreads = 384;
constexpr int kSlotBytes = 3072;
constexpr int kRing = 3;
constexpr int kSlots = 9;
constexpr int kWRow = 192;

constexpr int kOffWbuf = kSlots * 8 * kSlotBytes;
constexpr int kOffMl = kOffWbuf + 8 * kWRow * 4;
constexpr int kOffCpart = kOffMl + 20 * 4;
constexpr int kOffQf = kOffCpart + 2 * kWRow * 4;
constexpr int kOffXn = kOffQf + 2 * 96 * 4;
constexpr int kOffObf = kOffXn + 2 * 160 * 2;
constexpr int kOffFull = kOffObf + 2 * 48 * 2;
constexpr int kOffEmpty = kOffFull + kSlots * 8;
constexpr int kOffSync = kOffEmpty + kSlots * 8;
constexpr int kOffAnchor = kOffSync + 14 * 8;
constexpr int kOffOwn = kOffAnchor + 8;
constexpr int kSmemBytes = kOffOwn + 32;
static_assert(kSmemBytes <= 232448, "shared memory budget");
constexpr int kBarRows = 0, kBarFree = 8, kBarQ = 16, kBarXn = 32, kBarO = 48;
constexpr int kBarSentQ = 64, kBarSentP = 80, kBarSentY = 96;

constexpr int kMaxProg = 72;
constexpr int kMaxMerge = 32;
constexpr int kMaxLoads = 176;
constexpr int kAnchors = 5;

constexpr uint32_t kTau = 970;
constexpr uint32_t kTauHandoff = 1000;
constexpr uint32_t kTauWo = 833;
constexpr uint32_t kCredit = 700;
constexpr uint32_t kWindow = 4;
constexpr uint32_t kStartDelay = 1000;
constexpr uint32_t kLook = 3, kLookFar = 4;
constexpr uint32_t kDelayX = 2200, kDelayP = 1000, kDelayIdle = 3500, kPauseX = 200;

enum : uint32_t { OP_END = 0, OP_QPROJ = 1, OP_RFLOAD = 2, OP_SEG = 3, OP_OPROJ = 4 };
enum : uint32_t { MG_END = 0, MG_ATTN = 1, MG_Q = 2 };
enum : uint32_t {
    LD_KEEP = 1u << 3,
    LD_HANDOFF = 1u << 8,
    LD_VALID = 1u << 9,
    LD_HALF = 1u << 28,
    LD_ANCHOR = 1u << 29,
    LD_FAR = 1u << 30,
    LD_HIT = 1u << 31
};

struct alignas(64) Params {
    CUtensorMap tm[10];
    const __nv_bfloat16* x;
    const __nv_bfloat16* kA;
    __nv_bfloat16* out;
    uint32_t anchorDelay[kAnchors], anchorCredit[kAnchors];
    uint32_t prog[kMaxProg];
    uint32_t merge[kMaxMerge];
    uint32_t loads[kMaxLoads];
};

__device__ uint4 g_q[2][32][4][40];
__device__ uint4 g_p[2][32][4][4][18];
constexpr int kAccPackets = 216;
constexpr float kAccDone = 129.f;
constexpr int kAccPad = 2;
__device__ float4 g_acc[2][3][kAccPackets * kAccPad];
constexpr int kOutReplicas = 8;
__device__ float4 g_out[2][kOutReplicas][kAccPackets * kAccPad];

constexpr uint32_t kSpinLimit = 1u << 22;

__device__ __forceinline__ void mbar_init(uint32_t bar, uint32_t count) {
    asm volatile("mbarrier.init.shared::cta.b64 [%0], %1;" ::"r"(bar), "r"(count) : "memory");
}
__device__ __forceinline__ void mbar_arrive(uint32_t bar) {
    asm volatile("mbarrier.arrive.shared::cta.b64 _, [%0];" ::"r"(bar) : "memory");
}
__device__ __forceinline__ bool mbar_test(uint32_t bar, uint32_t parity) {
    uint32_t ok;
    asm volatile(
        "{\n\t.reg .pred p;\n\t"
        "mbarrier.test_wait.parity.shared::cta.b64 p, [%1], %2;\n\t"
        "selp.u32 %0, 1, 0, p;\n\t}"
        : "=r"(ok) : "r"(bar), "r"(parity) : "memory");
    return __all_sync(0xffffffffu, ok);
}
__device__ __forceinline__ void mbar_expect(uint32_t bar, uint32_t bytes) {
    asm volatile("mbarrier.arrive.expect_tx.shared::cta.b64 _, [%0], %1;" ::"r"(bar), "r"(bytes) : "memory");
}
__device__ __forceinline__ void mbar_wait(uint32_t bar, uint32_t parity) {
    uint32_t ok, it = 0;
    do {
        asm volatile(
            "{\n\t.reg .pred p;\n\t"
            "mbarrier.try_wait.parity.shared::cta.b64 p, [%1], %2;\n\t"
            "selp.u32 %0, 1, 0, p;\n\t}"
            : "=r"(ok) : "r"(bar), "r"(parity) : "memory");
        if (++it > kSpinLimit) __trap();
    } while (!ok);
}
__device__ __forceinline__ bool mbar_try(uint32_t bar, uint32_t parity) {
    uint32_t ok;
    asm volatile(
        "{\n\t.reg .pred p;\n\t"
        "mbarrier.try_wait.parity.shared::cta.b64 p, [%1], %2;\n\t"
        "selp.u32 %0, 1, 0, p;\n\t}"
        : "=r"(ok) : "r"(bar), "r"(parity) : "memory");
    return __all_sync(0xffffffffu, ok);
}
__device__ __forceinline__ void mbar_wait_u(uint32_t bar, uint32_t parity) {
    for (uint32_t it = 0; !mbar_try(bar, parity); it++)
        if (it > kSpinLimit) __trap();
}
__device__ __forceinline__ void tma3d(uint32_t dst, const CUtensorMap* tm, int c0, int c1, int c2, uint32_t bar, uint64_t pol) {
    asm volatile(
        "cp.async.bulk.tensor.3d.shared::cluster.global.mbarrier::complete_tx::bytes.L2::cache_hint "
        "[%0], [%1, {%2, %3, %4}], [%5], %6;"
        ::"r"(dst), "l"(tm), "r"(c0), "r"(c1), "r"(c2), "r"(bar), "l"(pol) : "memory");
}
__device__ __forceinline__ void tma3d_prefetch(const CUtensorMap* tm, int c0, int c1, int c2, uint64_t pol) {
    asm volatile("cp.async.bulk.prefetch.tensor.3d.L2.global.L2::cache_hint [%0, {%1, %2, %3}], %4;"
                 ::"l"(tm), "r"(c0), "r"(c1), "r"(c2), "l"(pol) : "memory");
}
__device__ __forceinline__ uint64_t make_policy(bool keep) {
    uint64_t pol;
    if (keep) asm volatile("createpolicy.fractional.L2::evict_normal.b64 %0, 1.0;" : "=l"(pol));
    else      asm volatile("createpolicy.fractional.L2::evict_first.b64 %0, 1.0;" : "=l"(pol));
    return pol;
}
__device__ __forceinline__ void ldsm4(uint32_t (&r)[4], uint32_t addr) {
    asm volatile("ldmatrix.sync.aligned.m8n8.x4.shared.b16 {%0,%1,%2,%3}, [%4];"
                 : "=r"(r[0]), "=r"(r[1]), "=r"(r[2]), "=r"(r[3]) : "r"(addr) : "memory");
}
__device__ __forceinline__ void ldsm4t(uint32_t (&r)[4], uint32_t addr) {
    asm volatile("ldmatrix.sync.aligned.m8n8.x4.trans.shared.b16 {%0,%1,%2,%3}, [%4];"
                 : "=r"(r[0]), "=r"(r[1]), "=r"(r[2]), "=r"(r[3]) : "r"(addr) : "memory");
}
__device__ __forceinline__ void mma16816(float (&c)[4], const uint32_t (&a)[4], uint32_t b0, uint32_t b1) {
    asm volatile("mma.sync.aligned.m16n8k16.row.col.f32.bf16.bf16.f32 {%0,%1,%2,%3}, {%4,%5,%6,%7}, {%8,%9}, {%0,%1,%2,%3};"
                 : "+f"(c[0]), "+f"(c[1]), "+f"(c[2]), "+f"(c[3])
                 : "r"(a[0]), "r"(a[1]), "r"(a[2]), "r"(a[3]), "r"(b0), "r"(b1));
}
__device__ __forceinline__ float bf16r(float v) { return __bfloat162float(__float2bfloat16_rn(v)); }
__device__ __forceinline__ uint32_t pack_bf16(float lo, float hi) {
    uint32_t r;
    asm("cvt.rn.bf16x2.f32 %0, %1, %2;" : "=r"(r) : "f"(hi), "f"(lo));
    return r;
}
__device__ __forceinline__ bool elect() {
    uint32_t p;
    asm volatile("{\n\t.reg .pred e;\n\telect.sync _|e, 0xffffffff;\n\tselp.u32 %0, 1, 0, e;\n\t}" : "=r"(p));
    return p;
}
__device__ __forceinline__ float fast_sqrt(float v) {
    float r;
    asm("sqrt.approx.f32 %0, %1;" : "=f"(r) : "f"(v));
    return r;
}
__device__ __forceinline__ float ex2(float v) {
    float r;
    asm("ex2.approx.ftz.f32 %0, %1;" : "=f"(r) : "f"(v));
    return r;
}
__device__ __forceinline__ void st_packet(uint4* p, uint32_t a, uint32_t b, uint32_t c, uint32_t tag) {
    asm volatile(
        "{\n\t.reg .b64 lo, hi;\n\t.reg .b128 v;\n\t"
        "mov.b64 lo, {%1, %2};\n\tmov.b64 hi, {%3, %4};\n\tmov.b128 v, {lo, hi};\n\t"
        "st.relaxed.gpu.global.b128 [%0], v;\n\t}"
        ::"l"(p), "r"(a), "r"(b), "r"(c), "r"(tag) : "memory");
}
__device__ __forceinline__ void st_packet(uint4* p, float a, float b, float c, uint32_t tag) {
    st_packet(p, __float_as_uint(a), __float_as_uint(b), __float_as_uint(c), tag);
}
__device__ __forceinline__ uint4 ld_packet(const uint4* p) {
    uint4 v;
    asm volatile(
        "{\n\t.reg .b64 lo, hi;\n\t.reg .b128 v;\n\t"
        "ld.relaxed.gpu.global.b128 v, [%4];\n\t"
        "mov.b128 {lo, hi}, v;\n\tmov.b64 {%0, %1}, lo;\n\tmov.b64 {%2, %3}, hi;\n\t}"
        : "=r"(v.x), "=r"(v.y), "=r"(v.z), "=r"(v.w) : "l"(p) : "memory");
    return v;
}
__device__ __forceinline__ void red_packet(float4* p, float a, float b, float c) {
    asm volatile("red.relaxed.gpu.global.add.v4.f32 [%0], {%1, %2, %3, %4};"
                 ::"l"(p), "f"(a), "f"(b), "f"(c), "f"(1.f) : "memory");
}
#define POLL_UNTIL(pause, loads, done)            \
    for (uint32_t it_ = 0;; it_++) {              \
        loads;                                    \
        if (__all_sync(0xffffffffu, done)) break; \
        if (it_ > kSpinLimit) __trap();           \
        if (pause) __nanosleep(pause);            \
    }
__device__ __forceinline__ uint32_t round24(float v) {
    const uint32_t u = __float_as_uint(v);
    return u + ((u & 0x7f800000u) == 0x7f800000u ? 0u : 0x80u);
}
__device__ __forceinline__ void st_packet5(uint4* p, const float* v, uint32_t tag) {
    const uint32_t r0 = round24(v[0]), r1 = round24(v[1]), r2 = round24(v[2]), r3 = round24(v[3]), r4 = round24(v[4]);
    st_packet(p, __byte_perm(r0, r1, 0x5321), __byte_perm(r1, r2, 0x6532), __byte_perm(r2, r3, 0x7653),
              (r4 >> 8) | (tag << 24));
}
__device__ __forceinline__ void add_packet5(float (&a)[5], const uint4& v) {
    a[0] += __uint_as_float(v.x << 8);
    a[1] += __uint_as_float(__funnelshift_r(v.x, v.y, 16) & 0xffffff00u);
    a[2] += __uint_as_float(__funnelshift_r(v.y, v.z, 8) & 0xffffff00u);
    a[3] += __uint_as_float(v.z & 0xffffff00u);
    a[4] += __uint_as_float(v.w << 8);
}
__device__ __forceinline__ uint32_t now_ns() {
    uint32_t t;
    asm volatile("mov.u32 %0, %globaltimer_lo;" : "=r"(t));
    return t;
}
__device__ __forceinline__ int fresh_lane() {
    int lane = threadIdx.x & 31;
    asm volatile("" : "+r"(lane));
    return lane;
}
__device__ __forceinline__ void pause_ns(uint32_t ns) {
    const uint32_t t0 = now_ns();
    while (now_ns() - t0 < ns) __nanosleep(100);
}
__device__ __forceinline__ float bf_lo(uint32_t v) { return __uint_as_float(v << 16); }
__device__ __forceinline__ float bf_hi(uint32_t v) { return __uint_as_float(v & 0xffff0000u); }
__device__ __forceinline__ float warp_sum(float v) {
#pragma unroll
    for (int o = 16; o > 0; o >>= 1) v += __shfl_xor_sync(0xffffffffu, v, o);
    return v;
}

constexpr float kScale = 0.07216878364870322f * 1.4426950408889634f;

struct Attn {
    float m, l;
    float acc[3][4];
};

__device__ __forceinline__ uint32_t probability(Attn& st, float s) {
    const float e = ex2(s - st.m);
    st.l += e;
    const float hi = bf16r(e);
    const uint32_t hl = pack_bf16(hi, e - hi);
    uint32_t pv;
    asm volatile("movmatrix.sync.aligned.m8n8.trans.b16 %0, %1;" : "=r"(pv) : "r"(hl));
    return pv;
}

__device__ __forceinline__ uint32_t softmax_step(Attn& st, float s) {
    if (__any_sync(0xffffffffu, s > st.m)) {
        float mx = fmaxf(s, __shfl_xor_sync(0xffffffffu, s, 4));
        mx = fmaxf(mx, __shfl_xor_sync(0xffffffffu, mx, 8));
        mx = fmaxf(mx, __shfl_xor_sync(0xffffffffu, mx, 16));
        mx = fmaxf(mx, st.m);
        const float corr = ex2(st.m - mx);
        st.m = mx;
        st.l *= corr;
#pragma unroll
        for (int a = 0; a < 3; a++)
#pragma unroll
            for (int i = 0; i < 4; i++) st.acc[a][i] *= corr;
    }
    return probability(st, s);
}

__global__ void __launch_bounds__(kThreads, 1)
fused_decode_kernel(const __grid_constant__ Params P) {
    extern __shared__ __align__(1024) unsigned char smem[];
    const uint32_t sbase = (uint32_t)__cvta_generic_to_shared(smem);
    const uint32_t sync0 = sbase + kOffSync;
    float* const wbuf = reinterpret_cast<float*>(smem + kOffWbuf);

    const int lane = threadIdx.x & 31;
    const int w = __shfl_sync(0xffffffffu, threadIdx.x >> 5, 0);
    const int cta = blockIdx.x;
    const int h = cta >> 2, jq = cta & 3;

    if (w >= 10) {
        const int i0 = 80 * (w - 10) + lane;
#pragma unroll
        for (int i = 0; i < 3; i++)
            if (i < 2 || lane < 16)
                asm volatile("cp.async.cg.shared.global [%0], [%1], 16;"
                             ::"r"(sbase + kOffWbuf + 16 * (i0 + 32 * i)), "l"(reinterpret_cast<const uint4*>(P.x) + i0 + 32 * i) : "memory");
    }
    if (elect()) {
        if (w == 8) {
#pragma unroll
            for (int i = 0; i < kSlots; i++) {
                mbar_init(sbase + kOffFull + 8 * i, 1);
                mbar_init(sbase + kOffEmpty + 8 * i, 8);
            }
        } else if (w == 9) {
            asm volatile("cp.async.bulk.prefetch.L2.global.L2::cache_hint [%0], %1, %2;"
                         ::"l"(P.kA + (size_t)((32 + h) * 4096 + 3072 + 256 * jq) * 192), "r"(8 * kSlotBytes),
                           "l"(make_policy(false)) : "memory");
#pragma unroll
            for (int i = 0; i < 10; i++) asm volatile("prefetch.tensormap [%0];" ::"l"(&P.tm[(i + 4) % 10]) : "memory");
        } else if (w == 10) {
#pragma unroll
            for (int i = 0; i < 14; i++) mbar_init(sync0 + 8 * i, (8 * i == kBarRows || 8 * i >= kBarSentY) ? 8 : 1);
        }
        if (w != 9) asm volatile("fence.mbarrier_init.release.cluster;" ::: "memory");
    }
    __syncwarp();
    if (w == 8) {
        asm volatile("bar.arrive 1, %0;" ::"n"(kThreads) : "memory");
    } else {
        asm volatile("bar.sync 1, %0;" ::"n"(kThreads) : "memory");
    }

    if (w < 8) {
        asm volatile("setmaxnreg.inc.sync.aligned.u32 232;");
        const uint32_t full0 = sbase + kOffFull;
        const uint32_t frag0 = sbase + w * 1024 + (lane & 7) * 128 + (((lane >> 3) ^ (lane & 7)) << 4), frag1 = frag0 ^ 64;
        auto frag_addr = [&](uint32_t s, int k) { return ((k & 1) ? frag1 : frag0) + s * (8 * kSlotBytes) + (k >> 1) * 8192; };
        uint32_t par = 0, rpos = 0, nrows = 0;
        auto wait_tile = [&](uint32_t s) { mbar_wait(full0 + 8 * s, (par >> s) & 1u); };
        auto tile_ready = [&](uint32_t s) { return mbar_test(full0 + 8 * s, (par >> s) & 1u); };
        auto release = [&](uint32_t s) {
            par ^= 1u << s;
            __syncwarp();
            if (elect()) mbar_arrive(full0 + 8 * s + (kOffEmpty - kOffFull));
        };
        auto ring_release = [&]() {
            release(rpos);
            if (++rpos == kRing) rpos = 0;
        };
        auto row_acquire = [&]() { mbar_wait(sync0 + kBarFree, (nrows & 1) ^ 1); };
        auto row_publish = [&]() {
            __syncwarp();
            if (elect()) mbar_arrive(sync0 + kBarRows);
            nrows++;
        };

        uint32_t rf[8][6][4];
#pragma unroll
        for (int i = 0; i < 8; i++)
#pragma unroll
            for (int s = 0; s < 6; s++)
#pragma unroll
                for (int k = 0; k < 4; k++) rf[i][s][k] = 0;

#pragma unroll 1
        for (int pc = 0;; pc++) {
            const uint32_t op = P.prog[pc];
            const uint32_t kind = op & 7u;
            if (kind == OP_END) break;
            const int lane = fresh_lane();
            const int g = lane >> 2, t = lane & 3;
            float* const row = wbuf + w * kWRow;

            if (kind == OP_SEG) {
                const uint32_t b = (op >> 3) & 1u;
                mbar_wait(sync0 + kBarQ + 8 * b, (op >> 4) & 1u);
                const uint2* qf = reinterpret_cast<const uint2*>(smem + kOffQf) + b * 48 + (lane & 7);
                Attn st;
                st.m = -INFINITY; st.l = 0.f;
#pragma unroll
                for (int a = 0; a < 3; a++)
#pragma unroll
                    for (int i = 0; i < 4; i++) st.acc[a][i] = 0.f;

                if (op & (1u << 7)) {
                    float c[4][4] = {};
#pragma unroll
                    for (int k = 0; k < 6; k++) {
                        const uint2 q = qf[8 * k];
#pragma unroll
                        for (int i = 0; i < 4; i++) mma16816(c[i], rf[2 * i][k], q.x, q.y);
                    }
                    float sc[4];
#pragma unroll
                    for (int i = 0; i < 4; i++) sc[i] = (c[i][0] + c[i][3]) * kScale;
                    float mx = fmaxf(fmaxf(sc[0], sc[1]), fmaxf(sc[2], sc[3]));
                    mx = fmaxf(mx, __shfl_xor_sync(0xffffffffu, mx, 4));
                    mx = fmaxf(mx, __shfl_xor_sync(0xffffffffu, mx, 8));
                    st.m = fmaxf(mx, __shfl_xor_sync(0xffffffffu, mx, 16));
                    uint32_t pv[4];
#pragma unroll
                    for (int i = 0; i < 4; i++) pv[i] = probability(st, sc[i]);
#pragma unroll
                    for (int i = 0; i < 4; i++)
#pragma unroll
                        for (int k = 0; k < 6; k++)
                            mma16816(st.acc[k >> 1], rf[2 * i + 1][k], (g >> 1) == 2 * (k & 1) ? pv[i] : 0u,
                                     (g >> 1) == 2 * (k & 1) + 1 ? pv[i] : 0u);
                }

                uint32_t lo = P.prog[pc + 1], hi = P.prog[pc + 2];
                pc += 2;
                bool haveK = false;
#pragma unroll 1
                while (lo & 15u) {
                    const bool rel = lo & 4u;
                    uint32_t sK = kRing - 2 + 2 * (lo & 3u), sV = sK + 1;
                    if (!(lo & 3u)) {
                        sK = rpos;
                        sV = rpos == kRing - 1 ? 0 : rpos + 1;
                        rpos = sV == kRing - 1 ? 0 : sV + 1;
                    }
                    lo = __funnelshift_r(lo, hi, 4);
                    hi >>= 4;
                    if (!haveK) wait_tile(sK);
                    const bool haveV = tile_ready(sV);
                    float c[2][4] = {};
#pragma unroll
                    for (int k = 0; k < 6; k++) {
                        uint32_t a[4];
                        ldsm4(a, frag_addr(sK, k));
                        const uint2 q = qf[8 * k];
                        mma16816(c[k & 1], a, q.x, q.y);
                    }
                    if (rel) release(sK);
                    const uint32_t pv = softmax_step(st, ((c[0][0] + c[0][3]) + (c[1][0] + c[1][3])) * kScale);
                    if (!haveV) wait_tile(sV);
                    haveK = tile_ready((lo & 3u) ? kRing - 2 + 2 * (lo & 3u) : rpos);
#pragma unroll
                    for (int k = 0; k < 6; k++) {
                        uint32_t a[4];
                        ldsm4t(a, frag_addr(sV, k));
                        mma16816(st.acc[k >> 1], a, (g >> 1) == 2 * (k & 1) ? pv : 0u, (g >> 1) == 2 * (k & 1) + 1 ? pv : 0u);
                    }
                    if (rel) release(sV);
                }

                float l = st.l;
                l += __shfl_xor_sync(0xffffffffu, l, 4);
                l += __shfl_xor_sync(0xffffffffu, l, 8);
                l += __shfl_xor_sync(0xffffffffu, l, 16);
                row_acquire();
#pragma unroll
                for (int a = 0; a < 3; a++) {
                    row[64 * a + 16 * t + g] = st.acc[a][0] + st.acc[a][1];
                    row[64 * a + 16 * t + g + 8] = st.acc[a][2] + st.acc[a][3];
                }
                if (lane == 0) { wbuf[8 * kWRow + w] = st.m; wbuf[8 * kWRow + 8 + w] = l; }
                row_publish();
            } else if (kind == OP_RFLOAD) {
#pragma unroll 1
                for (uint32_t tile = (op >> 3) & 7u; tile < (op >> 6); tile++) {
                    wait_tile(rpos);
#pragma unroll
                    for (int i = 0; i < 8; i++) {
                        if (tile == i) {
#pragma unroll
                            for (int k = 0; k < 6; k++) {
                                if (i & 1) ldsm4t(rf[i][k], frag_addr(rpos, k));
                                else ldsm4(rf[i][k], frag_addr(rpos, k));
                            }
                        }
                    }
                    ring_release();
                }
            } else if (kind == OP_QPROJ) {
                const uint32_t mask = (op >> 3) & 3u;
#pragma unroll 1
                for (uint32_t b = 0; b < 2; b++)
                    if ((mask >> b) & 1u) mbar_wait(sync0 + kBarXn + 8 * b, (op >> 5) & 1u);
                const uint32_t bb = mask == 3u ? (g & 1) : (mask >> 1);
                const uint32_t* xs = reinterpret_cast<const uint32_t*>(smem + kOffXn) + bb * 80 + 4 * w + t;
                float acc[3][4] = {};
#pragma unroll 1
                for (int p = 0; p < 3; p++) {
                    wait_tile(rpos);
                    if (p < 2 || w < 4) {
                        const uint32_t xv = xs[32 * p];
                        const uint32_t shrink = p == 2 ? 4096 : 0;
#pragma unroll
                        for (int k = 0; k < 6; k++) {
                            uint32_t a[4];
                            ldsm4t(a, frag_addr(rpos, k) - (k >> 1) * shrink);
                            mma16816(acc[k >> 1], a, (g >> 1) == 2 * (k & 1) ? xv : 0u, (g >> 1) == 2 * (k & 1) + 1 ? xv : 0u);
                        }
                    }
                    ring_release();
                }
#pragma unroll 1
                for (uint32_t b = 0; b < 2; b++) {
                    if (!((mask >> b) & 1u)) continue;
                    row_acquire();
#pragma unroll
                    for (int a = 0; a < 3; a++) {
                        row[64 * a + 16 * t + g] = b ? acc[a][1] : acc[a][0];
                        row[64 * a + 16 * t + g + 8] = b ? acc[a][3] : acc[a][2];
                    }
                    row_publish();
                }
            } else {
                const uint32_t mask = (op >> 3) & 3u;
                const uint32_t bb = mask == 3u ? (g & 1) : (mask >> 1);
                const uint32_t* ob = reinterpret_cast<const uint32_t*>(smem + kOffObf) + bb * 24 + t;
                const uint32_t roff = ((lane & 7) + 8 * (lane >> 4)) * 128 + ((((lane >> 3) & 1) ^ (lane & 7)) << 4);
                uint32_t sl[3];
#pragma unroll
                for (int p = 0; p < 3; p++) {
                    sl[p] = rpos;
                    if (++rpos == kRing) rpos = 0;
                }
                auto frag = [&](uint32_t (&a)[4], int p, int mt) {
                    ldsm4t(a, ((sbase + sl[p] * 8 * kSlotBytes + roff) ^ (((5 * w + mt) & 3) << 5)) + ((5 * w + mt) >> 2) * 2048);
                };
                uint32_t a0[5][4];
                wait_tile(sl[0]);
#pragma unroll
                for (int mt = 0; mt < 5; mt++) frag(a0[mt], 0, mt);
                release(sl[0]);
                wait_tile(sl[1]);
                wait_tile(sl[2]);
                row_acquire();
                if (mask & 1u) mbar_wait(sync0 + kBarO, (op >> 5) & 1u);
                if (mask & 2u) mbar_wait(sync0 + kBarO + 8, (op >> 5) & 1u);
                float c[3][4] = {};
#pragma unroll
                for (int p = 0; p < 3; p++) {
                    const uint32_t b0 = ob[8 * p], b1 = ob[8 * p + 4];
#pragma unroll
                    for (int mt = 0; mt < 5; mt++) {
                        if (p > 0) frag(a0[mt], p, mt);
                        const bool on = (g >> 1) == (mt & 3);
                        mma16816(c[mt == 4 ? 2 : (mt & 1)], a0[mt], on ? b0 : 0u, on ? b1 : 0u);
                    }
                    if (p > 0) release(sl[p]);
                }
                row[16 * t + g] = c[0][0] + c[1][0]; row[80 + 16 * t + g] = c[0][1] + c[1][1];
                row[16 * t + g + 8] = c[0][2] + c[1][2]; row[80 + 16 * t + g + 8] = c[0][3] + c[1][3];
                if (t == 0) {
                    row[64 + g] = c[2][0]; row[144 + g] = c[2][1];
                    row[72 + g] = c[2][2]; row[152 + g] = c[2][3];
                }
                __syncwarp();
                if (lane < 27) {
                    const bool last = ((op >> 5) & 3u) == 3u;
                    float4* dst = (last ? g_out[0][cta % kOutReplicas] : g_acc[0][(op >> 5) & 3u]) + (27 * w + lane) * kAccPad;
                    const float* y = row + 3 * lane;
                    if (mask & 1u) red_packet(dst, y[0], y[1], lane < 26 ? y[2] : 0.f);
                    if (mask & 2u) red_packet(dst + (last ? kOutReplicas : 3) * kAccPad * kAccPackets, y[80], y[81], lane < 26 ? y[82] : 0.f);
                }
                __syncwarp();
                if (lane < 2 && ((mask >> lane) & 1u)) mbar_arrive(sync0 + kBarSentY + 8 * lane);
            }
        }
    } else {
        asm volatile("setmaxnreg.dec.sync.aligned.u32 40;");
        if (w == 8) {
            if (elect()) {
#pragma unroll
                for (int p = 0; p < kRing; p++) {
                    const CUtensorMap* tm = &P.tm[p == 2 ? 8 : 4];
                    mbar_expect(sbase + kOffFull + 8 * p, p == 2 ? 4 * kSlotBytes : 8 * kSlotBytes);
                    tma3d(sbase + p * 8 * kSlotBytes, tm, 0, 160 * jq + 64 * p, 3 * h, sbase + kOffFull + 8 * p, make_policy(false));
                    tma3d_prefetch(tm, 0, 160 * jq + 64 * p, 3 * h, make_policy(true));
                }
            }
            __syncwarp();
            const int rowA = h * 4096 + 3072 + 256 * jq, rowB = h * 4096 + 1024 * jq;
            const int rowWq = 160 * jq, rowWo = 192 * h + 48 * jq;
            const uint64_t polKeep = make_policy(true), polStream = make_policy(false);
            const uint32_t rot = 64u * 11u * ((h & 3) + ((h >> 2) & 3) + (h >> 4));
            auto coord = [&](uint32_t e) {
                const uint32_t off = (e >> 10) & 0x3ffffu;
                const uint32_t offB = (off & ~0x3ffu) + ((off + rot) & 0x3c0u) + rowB;
                return (int)((e & 4u) ? off + ((e & 2u) ? rowWo : rowWq) : ((e & 2u) ? offB : off + rowA));
            };
            auto line = [&](uint32_t e) { return (e & 6u) == 4u ? 3 * h : 0; };
            auto map = [&](uint32_t e) { return &P.tm[(e & 7u) + ((e >> 26) & 4u)]; };
            auto interval = [&](uint32_t e) {
                return (e & 6u) == 6u ? kTauWo : ((e & LD_HANDOFF) ? kTauHandoff : kTau) >> ((e >> 28) & 1u);
            };
            uint32_t par = 7u, recent = 0xf012u, latest = 2, m = kRing + 1, na = 0, credit = kCredit, next = now_ns() + kStartDelay;
            auto landed = [&](uint32_t s) { return mbar_test(sbase + kOffFull + 8 * s, ((par >> s) & 1u) ^ 1u); };
            uint32_t e = P.loads[kRing];
            int c1 = coord(e);
#pragma unroll 1
            for (uint32_t n = kRing; e & LD_VALID; n++) {
                const uint32_t s = (e >> 4) & 15u;
                const uint32_t full = sbase + kOffFull + 8 * s;
                const uint32_t enext = P.loads[n + 1];
                if (m < n) m = n;
                for (uint32_t it = 0; !mbar_test(full + (kOffEmpty - kOffFull), ((par >> s) & 1u) ^ 1u); it++) {
                    if (it > 16 * kSpinLimit) __trap();
                    const uint32_t f = P.loads[m];
                    if (m >= n + ((e & LD_FAR) ? kLookFar : kLook) || !(f & LD_VALID)) continue;
                    if (f & LD_HIT) { m++; continue; }
                    const uint32_t now = now_ns();
                    if ((int)(now - next) >= 0 && landed(latest)) {
                        if (elect()) tma3d_prefetch(map(f), 0, coord(f), line(f), polStream);
                        next = now + interval(f);
                        m++;
                    }
                }
                if (e & LD_ANCHOR) {
                    const uint32_t t0 = __shfl_sync(0xffffffffu, *reinterpret_cast<volatile uint32_t*>(smem + kOffAnchor), 0) + P.anchorDelay[na];
                    if (m <= n || (int)(t0 - next) > 0) next = t0;
                    credit = P.anchorCredit[na++];
                }
                const bool fromHbm = !(e & LD_HIT) && m <= n;
                if (fromHbm) {
                    const uint32_t o = (recent >> (4 * kWindow - 4)) & 15u;
                    if (o != s && o != 15u) mbar_wait_u(sbase + kOffFull + 8 * o, ((par >> o) & 1u) ^ 1u);
                    uint32_t now = now_ns();
                    while ((int)(now - next) < 0) now = now_ns();
                    if ((int)(now - credit - next) > 0) next = now - credit;
                    next += interval(e);
                }
                if (elect()) {
                    mbar_expect(full, (e & 6u) == 6u ? 20480 : (8 * kSlotBytes) >> ((e >> 28) & 1u));
                    tma3d(sbase + s * 8 * kSlotBytes, map(e), 0, c1, line(e), full, polStream);
                    if (e & LD_KEEP) tma3d_prefetch(map(e), 0, c1, line(e), polKeep);
                }
                const uint32_t x = recent ^ (s * 0x1111u);
                recent |= (~(((x & 0x7777u) + 0x7777u) | x) & 0x8888u) * 15u >> 3;
                if (fromHbm) {
                    recent = (recent << 4) | s;
                    latest = s;
                }
                par ^= 1u << s;
                e = enext;
                c1 = coord(e);
            }
        } else {
            if (w == 9) {
#pragma unroll 1
                for (int n = 0;; n++) {
                    const uint32_t job = P.merge[n];
                    if ((job & 3u) == MG_END) break;
                    const uint32_t b = (job >> 2) & 1u;
                    const uint32_t tag = 1 + ((job >> 3) & 3u);
                    mbar_wait(sync0 + kBarRows, n & 1);
                    if ((job & 3u) == MG_Q) {
                        float o[5] = {}, e[5] = {};
                        const float* ext = wbuf + 2 * (lane & 3) * kWRow + 5 * min(32 + (lane >> 2), 38);
#pragma unroll
                        for (int k = 0; k < 5; k++) e[k] = ext[k] + ext[kWRow + k];
#pragma unroll
                        for (int i = 0; i < 8; i++)
#pragma unroll
                            for (int k = 0; k < 5; k++) o[k] += wbuf[i * kWRow + 5 * lane + k];
                        st_packet5(&g_q[b][h][jq][lane], o, tag);
#pragma unroll
                        for (int k = 0; k < 5; k++) {
                            e[k] += __shfl_xor_sync(0xffffffffu, e[k], 1);
                            e[k] += __shfl_xor_sync(0xffffffffu, e[k], 2);
                        }
                        if ((lane & 3) == 0) st_packet5(&g_q[b][h][jq][32 + (lane >> 2)], e, tag);
                        __syncwarp();
                        if (lane == 0) mbar_arrive(sync0 + kBarSentQ + 8 * b);
                    } else {
                        float2* cp = reinterpret_cast<float2*>(smem + kOffCpart) + b * (kWRow / 2) + 3 * lane;
                        float2* cml = reinterpret_cast<float2*>(smem + kOffMl + 64) + b;
                        const float4* ml = reinterpret_cast<const float4*>(smem + kOffMl);
                        const bool merge = !(job & 32u);
                        const float2 pml = merge ? *cml : make_float2(-INFINITY, 0.f);
                        const float4 m0 = ml[0], m1 = ml[1];
                        float sc[8] = {m0.x, m0.y, m0.z, m0.w, m1.x, m1.y, m1.z, m1.w};
                        const float M = fmaxf(fmaxf(fmaxf(fmaxf(sc[0], sc[1]), fmaxf(sc[2], sc[3])),
                                                    fmaxf(fmaxf(sc[4], sc[5]), fmaxf(sc[6], sc[7]))), pml.x);
#pragma unroll
                        for (int i = 0; i < 8; i++) sc[i] = ex2(sc[i] - M);
                        const float ps = ex2(pml.x - M);
                        float2 o[3];
#pragma unroll
                        for (int k = 0; k < 3; k++) {
                            o[k] = merge ? cp[k] : make_float2(0.f, 0.f);
                            o[k].x *= ps; o[k].y *= ps;
                        }
#pragma unroll
                        for (int i = 0; i < 8; i++)
#pragma unroll
                            for (int k = 0; k < 3; k++) {
                                const float2 v = reinterpret_cast<const float2*>(wbuf)[i * (kWRow / 2) + 3 * lane + k];
                                o[k].x = fmaf(v.x, sc[i], o[k].x);
                                o[k].y = fmaf(v.y, sc[i], o[k].y);
                            }
                        const float4 l0 = ml[2], l1 = ml[3];
                        const float L = fmaf(pml.y, ps, ((l0.x * sc[0] + l0.y * sc[1]) + (l0.z * sc[2] + l0.w * sc[3])) +
                                                        ((l1.x * sc[4] + l1.y * sc[5]) + (l1.z * sc[6] + l1.w * sc[7])));
                        if (job & 64u) {
                            uint4* dst = &g_p[b][h][lane >> 3][jq][2 * (lane & 7)];
                            st_packet(dst, o[0].x, o[0].y, o[1].x, tag);
                            st_packet(dst + 1, o[1].y, o[2].x, o[2].y, tag);
                            if (lane < 8) st_packet(&g_p[b][h][lane >> 1][jq][16 + (lane & 1)], M, L, 0.f, tag);
                            if (lane == 0) mbar_arrive(sync0 + kBarSentP + 8 * b);
                        } else {
#pragma unroll
                            for (int k = 0; k < 3; k++) cp[k] = o[k];
                            __syncwarp();
                            if (lane == 0) *cml = make_float2(M, L);
                        }
                    }
                    __syncwarp();
                    if (lane == 0) mbar_arrive(sync0 + kBarFree);
                }
            } else {
                const uint32_t b = w - 10;
                __nv_bfloat16* const xn = reinterpret_cast<__nv_bfloat16*>(smem + kOffXn) + b * 160;
                __nv_bfloat16* const qd = reinterpret_cast<__nv_bfloat16*>(smem + kOffQf) + b * 192;
                __nv_bfloat16* const ob = reinterpret_cast<__nv_bfloat16*>(smem + kOffObf) + b * 48;
                uint2* const own = reinterpret_cast<uint2*>(smem + kOffOwn) + 2 * b;
#pragma unroll 1
                for (uint32_t layer = 0; layer < 4; layer++) {
                    const uint32_t tag = layer + 1;
                    {
                        int lane = fresh_lane();
                        uint32_t x01[7], x2[7];
                        if (layer == 0) {
                            const uint4* stage = reinterpret_cast<const uint4*>(wbuf) + 80 * b;
                            asm volatile("cp.async.wait_all;" ::: "memory");
                            __syncwarp();
#pragma unroll
                            for (int i = 0; i < 7; i++) {
                                const int p = lane + 32 * i, u = p % 27;
                                const unsigned short* xp = reinterpret_cast<const unsigned short*>(stage) + (p / 27) * 80 + 3 * u;
                                x01[i] = p < kAccPackets ? xp[0] | ((uint32_t)xp[1] << 16) : 0u;
                                x2[i] = (p < kAccPackets && u < 26) ? xp[2] : 0u;
                            }
                        } else {
                            mbar_wait(sync0 + kBarSentY + 8 * b, (layer - 1) & 1);
                            pause_ns(kDelayX);
                            uint4 v[7];
                            const uint4* src = reinterpret_cast<const uint4*>(&g_acc[b][layer - 1][lane * kAccPad]);
                            const uint32_t done = __float_as_uint(kAccDone);
                            POLL_UNTIL(kPauseX, v[0] = ld_packet(src + (27 * (cta & 7) + min(lane, 26) - lane) * kAccPad), v[0].w == done);
                            POLL_UNTIL(kPauseX,
                                v[0] = ld_packet(src); v[1] = ld_packet(src + 32 * kAccPad); v[2] = ld_packet(src + 64 * kAccPad);
                                v[3] = ld_packet(src + 96 * kAccPad); v[4] = ld_packet(src + 128 * kAccPad);
                                v[5] = ld_packet(src + 160 * kAccPad); v[6] = ld_packet(src + (lane < 24 ? 192 * kAccPad : 0)),
                                v[0].w == done && v[1].w == done && v[2].w == done && v[3].w == done && v[4].w == done &&
                                    v[5].w == done && v[6].w == done);
#pragma unroll
                            for (int i = 0; i < 7; i++) {
                                x01[i] = pack_bf16(__uint_as_float(v[i].x), __uint_as_float(v[i].y));
                                x2[i] = pack_bf16(__uint_as_float(v[i].z), 0.f);
                            }
                            if (lane >= 24) x01[6] = x2[6] = 0u;
                        }
#pragma unroll
                        for (int i = 0; i < 7; i++) {
                            const int p = lane + 32 * i;
                            if ((p & 127) == cta && p < kAccPackets) {
                                own[i >> 2] = make_uint2(x01[i], x2[i]);
                            }
                        }
                        float sum = 0.f;
#pragma unroll
                        for (int i = 0; i < 7; i++) sum += (bf_lo(x01[i]) + bf_hi(x01[i])) + bf_lo(x2[i]);
                        const float mean = warp_sum(sum) * (1.f / 640.f);
                        float sq = 0.f;
#pragma unroll
                        for (int i = 0; i < 7; i++) {
                            const bool none = i == 6 && lane >= 24;
                            const float d0 = none ? 0.f : bf_lo(x01[i]) - mean, d1 = none ? 0.f : bf_hi(x01[i]) - mean;
                            const bool last = lane == 26 - 5 * i || lane == 53 - 5 * i;
                            const float d2 = (none || last) ? 0.f : bf_lo(x2[i]) - mean;
                            sq += fmaf(d0, d0, fmaf(d1, d1, d2 * d2));
                        }
                        const float var = warp_sum(sq) * (1.f / 640.f);
                        const float meanb = bf16r(mean);
                        const float rden = __fdividef(1.f, bf16r(fast_sqrt(bf16r(bf16r(var) + 1e-5f))));
#pragma unroll
                        for (int i = 0; i < 7; i++) {
                            const uint32_t q = lane + 32 * i - 54 * jq;
                            if (q < 54u) {
                                const int c = 3 * q - (q >= 27u);
                                xn[c] = __float2bfloat16_rn(bf16r(bf_lo(x01[i]) - meanb) * rden);
                                xn[c + 1] = __float2bfloat16_rn(bf16r(bf_hi(x01[i]) - meanb) * rden);
                                if (q != 26u && q != 53u) xn[c + 2] = __float2bfloat16_rn(bf16r(bf_lo(x2[i]) - meanb) * rden);
                            }
                        }
                        if (lane == 0) *reinterpret_cast<volatile uint32_t*>(smem + kOffAnchor) = now_ns();
                        __syncwarp();
                        if (lane == 0) mbar_arrive(sync0 + kBarXn + 8 * b);
                        if (layer >= 2 && lane < 4 && cta + 128 * (lane >> 1) < kAccPackets)
                            g_acc[b][layer - 2][(cta + 128 * (lane >> 1)) * kAccPad + (lane & 1)] = make_float4(0.f, 0.f, 0.f, 0.f);
                        __syncwarp();
                    }
                    {
                        const int lane = fresh_lane();
                        mbar_wait(sync0 + kBarSentQ + 8 * b, layer & 1);
                        if (layer == 0 || (layer == 1 && b == 1)) pause_ns(kDelayIdle);
                        uint4 v[5];
                        const uint4* src = &g_q[b][h][0][lane];
                        const uint4* ext = &g_q[b][h][lane & 3][lane < 28 ? 32 + (lane >> 2) : 38];
                        POLL_UNTIL(0,
                            v[0] = ld_packet(src); v[1] = ld_packet(src + 40); v[2] = ld_packet(src + 80);
                            v[3] = ld_packet(src + 120); v[4] = ld_packet(ext),
                            (v[0].w >> 24) == tag && (v[1].w >> 24) == tag && (v[2].w >> 24) == tag &&
                                (v[3].w >> 24) == tag && (v[4].w >> 24) == tag);
                        __syncwarp();
                        auto store_q = [&](int d, float q) {
                            qd[(d & ~31) + ((d >> 3) & 1) * 16 + ((d >> 1) & 3) * 4 + ((d >> 4) & 1) * 2 + (d & 1)] =
                                __float2bfloat16_rn(q);
                        };
                        float a[5] = {};
#pragma unroll
                        for (int i = 0; i < 4; i++) add_packet5(a, v[i]);
#pragma unroll
                        for (int k = 0; k < 5; k++) store_q(5 * lane + k, a[k]);
                        float e[5] = {};
                        add_packet5(e, v[4]);
#pragma unroll
                        for (int k = 0; k < 5; k++) {
                            e[k] += __shfl_xor_sync(0xffffffffu, e[k], 1);
                            e[k] += __shfl_xor_sync(0xffffffffu, e[k], 2);
                            const int d = 160 + 5 * (lane >> 2) + k;
                            if ((lane & 3) == 0 && d < 192) store_q(d, e[k]);
                        }
                        __syncwarp();
                        if (lane == 0) mbar_arrive(sync0 + kBarQ + 8 * b);
                    }
                    {
                        const int lane = fresh_lane();
                        mbar_wait(sync0 + kBarSentP + 8 * b, layer & 1);
                        pause_ns((b == 0 && (layer == 0 || layer == 3)) ? kDelayIdle : (layer == 3 ? 0 : kDelayP));
                        uint4 v0, v1, ml;
                        const uint4* src = &g_p[b][h][jq][2 * (lane >> 4)][lane & 15];
                        const uint4* mls = &g_p[b][h][jq][lane & 3][16];
                        POLL_UNTIL(0, v0 = ld_packet(src); v1 = ld_packet(src + 18); ml = ld_packet(mls),
                                   v0.w == tag && v1.w == tag && ml.w == tag);
                        __syncwarp();
                        const float mi = __uint_as_float(ml.x);
                        float M = fmaxf(mi, __shfl_xor_sync(0xffffffffu, mi, 1));
                        M = fmaxf(M, __shfl_xor_sync(0xffffffffu, M, 2));
                        const float sc = ex2(mi - M);
                        float L = __uint_as_float(ml.y) * sc;
                        L += __shfl_xor_sync(0xffffffffu, L, 1);
                        L += __shfl_xor_sync(0xffffffffu, L, 2);
                        const float s0 = __shfl_sync(0xffffffffu, sc, 2 * (lane >> 4));
                        const float s1 = __shfl_sync(0xffffffffu, sc, 2 * (lane >> 4) + 1);
                        float o0 = fmaf(__uint_as_float(v0.x), s0, __uint_as_float(v1.x) * s1);
                        float o1 = fmaf(__uint_as_float(v0.y), s0, __uint_as_float(v1.y) * s1);
                        float o2 = fmaf(__uint_as_float(v0.z), s0, __uint_as_float(v1.z) * s1);
                        o0 += __shfl_xor_sync(0xffffffffu, o0, 16);
                        o1 += __shfl_xor_sync(0xffffffffu, o1, 16);
                        o2 += __shfl_xor_sync(0xffffffffu, o2, 16);
                        if (lane < 16) {
                            ob[3 * lane] = __float2bfloat16_rn(__fdividef(o0, L));
                            ob[3 * lane + 1] = __float2bfloat16_rn(__fdividef(o1, L));
                            ob[3 * lane + 2] = __float2bfloat16_rn(__fdividef(o2, L));
                        }
                        __syncwarp();
                        if (lane == 0) mbar_arrive(sync0 + kBarO + 8 * b);
                        const int p = cta + 128 * lane;
                        if (p < kAccPackets) {
                            const uint2 v = own[lane];
                            red_packet((layer == 3 ? g_out[b][0] : g_acc[b][layer]) + p * kAccPad, bf_lo(v.x), bf_hi(v.x), bf_lo(v.y));
                        }
                    }
                }
                {
                    mbar_wait(sync0 + kBarSentY + 8 * b, 1);
                    const int p = cta + 128 * ((lane / kOutReplicas) & 1), r = lane % kOutReplicas;
                    float4* src = &g_out[b][r][(p < kAccPackets ? p : cta) * kAccPad];
                    const float want = kCtas / kOutReplicas + (r == 0);
                    uint4 v;
                    for (uint32_t it = 0;; it++) {
                        v = ld_packet(reinterpret_cast<const uint4*>(src));
                        if (__all_sync(0xffffffffu, v.w == __float_as_uint(want))) break;
                        if (it > kSpinLimit) __trap();
                    }
                    float o0 = __uint_as_float(v.x), o1 = __uint_as_float(v.y), o2 = __uint_as_float(v.z);
#pragma unroll
                    for (int o = 1; o < kOutReplicas; o <<= 1) {
                        o0 += __shfl_xor_sync(0xffffffffu, o0, o);
                        o1 += __shfl_xor_sync(0xffffffffu, o1, o);
                        o2 += __shfl_xor_sync(0xffffffffu, o2, o);
                    }
                    if (lane < 2 * kOutReplicas && p < kAccPackets) {
                        if (r < 3 - (p % 27 == 26))
                            P.out[b * 640 + (p / 27) * 80 + 3 * (p % 27) + r] = __float2bfloat16_rn(r == 0 ? o0 : r == 1 ? o1 : o2);
                        *src = make_float4(0.f, 0.f, 0.f, 0.f);
                        if (r == 0) g_acc[b][2][p * kAccPad] = make_float4(0.f, 0.f, 0.f, 0.f);
                    }
                }
            }
        }
    }
}


struct Sched {
    Params& P;
    int np = 0, nm = 0, nl = 0, rslot = 0, mark = 0;
    uint32_t pending = 0;
    enum { RF = 1 << 7, FIRST = 1 << 11, PUB = 1 << 12 };

    void handoff_begin() { mark = nl; }
    void handoff_end() { for (int i = mark; i < nl; i++) P.loads[i] |= LD_HANDOFF; }
    void slot(uint32_t e, int s) { P.loads[nl++] = e | (s << 4); }
    void ring(uint32_t e) {
        slot(e | pending, rslot);
        pending = 0;
        rslot = (rslot + 1) % kRing;
    }
    static uint32_t tile(int isB, int b, int idx, int v) {
        return LD_VALID | (2 * isB + v) | (uint32_t)(b * 32 * 4096 + 64 * idx) << 10;
    }
    void pair(int isB, int b, int idx, uint32_t fk = 0, uint32_t fv = 0) {
        ring(tile(isB, b, idx, 0) | fk);
        ring(tile(isB, b, idx, 1) | fv);
    }
    void qproj(int mask, int layer, uint32_t f) {
        for (int p = 0; p < 3; p++) ring(LD_VALID | (4 + (layer & 1)) | (64 * p) << 10 | (p == 2 ? LD_HALF : 0u) | f);
        if (layer > 0) pending = LD_ANCHOR;
        P.prog[np++] = OP_QPROJ | (mask << 3) | (layer << 5);
        for (int b = 0; b < 2; b++)
            if ((mask >> b) & 1) P.merge[nm++] = MG_Q | (b << 2) | (layer << 3);
    }
    void oproj(int mask, int layer, uint32_t fLast) {
        for (int p = 0; p < 3; p++) ring(LD_VALID | (6 + (layer & 1)) | (16 * p) << 10 | (p == 2 ? fLast : 0u));
        P.prog[np++] = OP_OPROJ | (mask << 3) | (layer << 5);
    }
    void rfload(int from, int to, int isB, int b, int idx0) {
        for (int i = from; i < to; i++) ring(tile(isB, b, idx0 + i / 2, i & 1));
        P.prog[np++] = OP_RFLOAD | (from << 3) | (to << 6);
    }
    void seg(int b, int layer, uint32_t flags, const char* order) {
        uint64_t list = 0;
        for (int n = 0; order[n]; n++) {
            const char c = order[n];
            uint64_t item = 12;
            if (c >= 'a' && c <= 'c') item = 12 | (c - 'a' + 1);
            if (c >= 'A' && c <= 'C') item = 8 | (c - 'A' + 1);
            list |= item << (4 * n);
        }
        P.prog[np++] = OP_SEG | (b << 3) | ((layer & 1) << 4) | (flags & RF);
        P.prog[np++] = (uint32_t)list;
        P.prog[np++] = (uint32_t)(list >> 32);
        P.merge[nm++] = MG_ATTN | (b << 2) | (layer << 3) | ((flags & FIRST) ? 32 : 0) | ((flags & PUB) ? 64 : 0);
    }
};

void build_schedule(Params& P) {
    for (int i = 0; i < kMaxProg; i++) P.prog[i] = OP_END;
    for (int i = 0; i < kMaxMerge; i++) P.merge[i] = MG_END;
    for (int i = 0; i < kMaxLoads; i++) P.loads[i] = 0;
    const uint32_t anchorDelay[kAnchors] = {200, 200, 200, 200, 0};
    const uint32_t anchorCredit[kAnchors] = {kCredit, 2500, 2500, kCredit, 300};
    for (int i = 0; i < kAnchors; i++) {
        P.anchorDelay[i] = anchorDelay[i];
        P.anchorCredit[i] = anchorCredit[i];
    }

    Sched S{P};
    using F = Sched;
    const int keep[2] = {9, 10};
    auto kept = [&](int b, int idx, int v, uint32_t f) { return (2 * (15 - idx) + (1 - v)) < keep[b] ? f : 0u; };
    int nextD[2] = {3, 7}, nextH[2] = {11, 11}, nextK = 11;
    auto fill = [&](int b, int layer, int n, uint32_t flags = 0) {
        for (int i = 0; i < n; i++) S.pair(1, b, nextD[b]++);
        S.seg(b, layer, flags, &"dd"[2 - n]);
    };
    auto mixed = [&](int b, int layer, uint32_t flags, const char* order, int refill0, const int* pos) {
        int tiles = 0, done = 0, dst[6], n = 0;
        for (const char* c = order; *c; c++)
            if (*c >= 'a' && *c <= 'c') { dst[n++] = kRing + 2 * (*c - 'a'); dst[n++] = kRing + 2 * (*c - 'a') + 1; }
        for (const char* c = order; *c; c++) {
            if (*c != 'h' && *c != 'd' && *c != 'k') continue;
            const int idx = *c == 'h' ? nextH[b]++ : *c == 'k' ? nextK++ : nextD[b]++;
            for (int v = 0; v < 2; v++, tiles++) {
                for (; done < n && pos[done] <= tiles; done++) S.slot(F::tile(1, 1, refill0 + done / 2, done & 1) | LD_FAR, dst[done]);
                S.ring(F::tile(1, b, idx, v) | LD_FAR | kept(b, idx, v, *c == 'h' ? LD_HIT : *c == 'k' ? LD_KEEP : 0u));
            }
        }
        S.seg(b, layer, flags, order);
    };

    S.qproj(3, 0, LD_KEEP);
    S.slot(F::tile(0, 1, 0, 0), kRing);
    S.slot(F::tile(0, 1, 0, 1), kRing + 1);
    S.rfload(0, 8, 0, 0, 0);
    S.seg(0, 0, F::RF | F::FIRST | F::PUB, "");
    S.handoff_begin();
    for (int i = 1; i < 4; i++) S.pair(0, 1, i);
    S.seg(1, 0, F::FIRST | F::PUB, "addd");
    S.oproj(3, 0, LD_KEEP);
    for (int i = 0; i < 4; i++) S.slot(F::tile(1, 0, i / 2, i & 1), kRing + i);
    S.qproj(3, 1, LD_KEEP);
    for (int i = 4; i < 6; i++) S.slot(F::tile(1, 0, i / 2, i & 1), kRing + i);
    S.handoff_end();
    for (int i = 3; i < 16; i++) S.pair(1, 0, i, kept(0, i, 0, LD_KEEP), kept(0, i, 1, LD_KEEP));
    S.seg(0, 1, F::FIRST | F::PUB, "dddAdddBdddCdddd");
    S.handoff_begin();
    S.oproj(1, 1, 0);
    fill(1, 1, 2, F::FIRST);
    S.qproj(1, 2, LD_HIT);
    fill(1, 1, 1);
    S.seg(0, 2, F::RF | F::FIRST | F::PUB, "");
    S.rfload(0, 2, 1, 1, 3);
    S.oproj(1, 2, LD_HIT);
    S.rfload(2, 6, 1, 1, 3);
    fill(1, 1, 1);
    S.qproj(1, 3, LD_HIT);
    S.rfload(6, 8, 1, 1, 3);
    S.handoff_end();
    const int pos4[6] = {3, 3, 4, 5, 7, 7};
    mixed(0, 3, F::FIRST, "ahbhchhh", 0, pos4);
    mixed(1, 1, F::RF | F::PUB, "kkABkCkk", 0, nullptr);
    S.handoff_begin();
    S.oproj(2, 1, LD_KEEP);
    fill(0, 3, 2);
    S.qproj(2, 2, 0);
    fill(0, 3, 1);
    for (int i = 0; i < 4; i++) S.pair(0, 1, i);
    S.seg(1, 2, F::FIRST | F::PUB, "dddd");
    fill(0, 3, 1);
    S.oproj(2, 2, 0);
    fill(0, 3, 2);
    S.qproj(2, 3, 0);
    S.handoff_end();
    mixed(0, 3, F::PUB, "dd", 0, nullptr);
    const int pos6[6] = {3, 4, 7, 9, 10, 11};
    nextD[1] = 10;
    mixed(1, 3, F::RF | F::FIRST | F::PUB, "adbhchhAhBhC", 7, pos6);
    S.oproj(3, 3, LD_HIT);
}

typedef CUresult (*EncodeFn)(CUtensorMap*, CUtensorMapDataType, cuuint32_t, void*, const cuuint64_t*,
                             const cuuint64_t*, const cuuint32_t*, const cuuint32_t*, CUtensorMapInterleave,
                             CUtensorMapSwizzle, CUtensorMapL2promotion, CUtensorMapFloatOOBfill);

}

extern "C" void kernel_launch(void* const* d_in, const int* in_sizes, int n_in, void* d_out, int out_size) {
    (void)in_sizes; (void)n_in; (void)out_size;
    Params P;
    void* fn = nullptr;
    cudaDriverEntryPointQueryResult qr;
    cudaGetDriverEntryPoint("cuTensorMapEncodeTiled", &fn, cudaEnableDefault, &qr);
    EncodeFn encode = reinterpret_cast<EncodeFn>(fn);
    auto make_map = [&](int i, void* base, cuuint64_t rows, cuuint64_t rowBytes, cuuint64_t lines, cuuint32_t boxRows,
                        cuuint32_t boxLines) {
        const cuuint64_t dims[3] = {64, rows, lines};
        const cuuint64_t strides[2] = {rowBytes, 128};
        const cuuint32_t box[3] = {64, boxRows, boxLines};
        const cuuint32_t es[3] = {1, 1, 1};
        encode(&P.tm[i], CU_TENSOR_MAP_DATA_TYPE_BFLOAT16, 3, base, dims, strides, box, es, CU_TENSOR_MAP_INTERLEAVE_NONE,
               CU_TENSOR_MAP_SWIZZLE_128B, CU_TENSOR_MAP_L2_PROMOTION_NONE, CU_TENSOR_MAP_FLOAT_OOB_FILL_NONE);
    };
    for (int i = 0; i < 2; i++) {
        void* const* in = d_in + 5 * i;
        make_map(2 * i, in[1], 2 * 32 * 4096, 384, 3, 64, 3);
        make_map(2 * i + 1, in[2], 2 * 32 * 4096, 384, 3, 64, 3);
        make_map(4 + i, in[3], 640, 12288, 96, 64, 3);
        make_map(8 + i, in[3], 640, 12288, 96, 32, 3);
        make_map(6 + i, in[4], 6144, 1280, 10, 16, 10);
    }
    P.x = static_cast<const __nv_bfloat16*>(d_in[0]);
    P.kA = static_cast<const __nv_bfloat16*>(d_in[1]);
    P.out = static_cast<__nv_bfloat16*>(d_out);
    build_schedule(P);
    cudaFuncSetAttribute(fused_decode_kernel, cudaFuncAttributeMaxDynamicSharedMemorySize, kSmemBytes);
    fused_decode_kernel<<<kCtas, kThreads, kSmemBytes>>>(P);
}
```

```cpp
#include <cuda_runtime.h>
#include <cuda_bf16.h>
#include <cuda.h>
#include <stdint.h>

namespace {

constexpr int kCtas = 128;
constexpr int kThreads = 384;
constexpr int kSlotBytes = 3072;
constexpr int kRing = 3;
constexpr int kSlots = 9;
constexpr int kWRow = 192;

constexpr int kOffWbuf = kSlots * 8 * kSlotBytes;
constexpr int kOffMl = kOffWbuf + 8 * kWRow * 4;
constexpr int kOffCpart = kOffMl + 20 * 4;
constexpr int kOffQf = kOffCpart + 2 * kWRow * 4;
constexpr int kOffXn = kOffQf + 2 * 96 * 4;
constexpr int kOffObf = kOffXn + 2 * 160 * 2;
constexpr int kOffFull = kOffObf + 2 * 48 * 2;
constexpr int kOffEmpty = kOffFull + kSlots * 8;
constexpr int kOffSync = kOffEmpty + kSlots * 8;
constexpr int kOffAnchor = kOffSync + 14 * 8;
constexpr int kOffOwn = kOffAnchor + 8;
constexpr int kSmemBytes = kOffOwn + 32;
static_assert(kSmemBytes <= 232448, "shared memory budget");
constexpr int kBarRows = 0, kBarFree = 8, kBarQ = 16, kBarXn = 32, kBarO = 48;
constexpr int kBarSentQ = 64, kBarSentP = 80, kBarSentY = 96;

constexpr int kMaxProg = 72;
constexpr int kMaxMerge = 32;
constexpr int kMaxLoads = 176;
constexpr int kAnchors = 5;

constexpr uint32_t kTau = 970;
constexpr uint32_t kTauHandoff = 1000;
constexpr uint32_t kTauWo = 833;
constexpr uint32_t kCredit = 700;
constexpr uint32_t kWindow = 4;
constexpr uint32_t kStartDelay = 1000;
constexpr uint32_t kLook = 3, kLookFar = 4;
constexpr uint32_t kDelayX = 2200, kDelayP = 1000, kDelayIdle = 3500, kPauseX = 200;

enum : uint32_t { OP_END = 0, OP_QPROJ = 1, OP_RFLOAD = 2, OP_SEG = 3, OP_OPROJ = 4 };
enum : uint32_t { MG_END = 0, MG_ATTN = 1, MG_Q = 2 };
enum : uint32_t {
    LD_KEEP = 1u << 3,
    LD_HANDOFF = 1u << 8,
    LD_VALID = 1u << 9,
    LD_HALF = 1u << 28,
    LD_ANCHOR = 1u << 29,
    LD_FAR = 1u << 30,
    LD_HIT = 1u << 31
};

struct alignas(64) Params {
    CUtensorMap tm[10];
    const __nv_bfloat16* x;
    const __nv_bfloat16* kA;
    __nv_bfloat16* out;
    uint32_t anchorDelay[kAnchors], anchorCredit[kAnchors];
    uint32_t prog[kMaxProg];
    uint32_t merge[kMaxMerge];
    uint32_t loads[kMaxLoads];
};

__device__ uint4 g_q[2][32][4][40];
__device__ uint4 g_p[2][32][4][4][18];
constexpr int kAccPackets = 216;
constexpr float kAccDone = 129.f;
constexpr int kAccPad = 2;
__device__ float4 g_acc[2][3][kAccPackets * kAccPad];
constexpr int kOutReplicas = 8;
__device__ float4 g_out[2][kOutReplicas][kAccPackets * kAccPad];

constexpr uint32_t kSpinLimit = 1u << 22;

__device__ __forceinline__ void mbar_init(uint32_t bar, uint32_t count) {
    asm volatile("mbarrier.init.shared::cta.b64 [%0], %1;" ::"r"(bar), "r"(count) : "memory");
}
__device__ __forceinline__ void mbar_arrive(uint32_t bar) {
    asm volatile("mbarrier.arrive.shared::cta.b64 _, [%0];" ::"r"(bar) : "memory");
}
__device__ __forceinline__ bool mbar_test(uint32_t bar, uint32_t parity) {
    uint32_t ok;
    asm volatile(
        "{\n\t.reg .pred p;\n\t"
        "mbarrier.test_wait.parity.shared::cta.b64 p, [%1], %2;\n\t"
        "selp.u32 %0, 1, 0, p;\n\t}"
        : "=r"(ok) : "r"(bar), "r"(parity) : "memory");
    return __all_sync(0xffffffffu, ok);
}
__device__ __forceinline__ void mbar_expect(uint32_t bar, uint32_t bytes) {
    asm volatile("mbarrier.arrive.expect_tx.shared::cta.b64 _, [%0], %1;" ::"r"(bar), "r"(bytes) : "memory");
}
__device__ __forceinline__ void mbar_wait(uint32_t bar, uint32_t parity) {
    uint32_t ok, it = 0;
    do {
        asm volatile(
            "{\n\t.reg .pred p;\n\t"
            "mbarrier.try_wait.parity.shared::cta.b64 p, [%1], %2;\n\t"
            "selp.u32 %0, 1, 0, p;\n\t}"
            : "=r"(ok) : "r"(bar), "r"(parity) : "memory");
        if (++it > kSpinLimit) __trap();
    } while (!ok);
}
__device__ __forceinline__ bool mbar_try(uint32_t bar, uint32_t parity) {
    uint32_t ok;
    asm volatile(
        "{\n\t.reg .pred p;\n\t"
        "mbarrier.try_wait.parity.shared::cta.b64 p, [%1], %2;\n\t"
        "selp.u32 %0, 1, 0, p;\n\t}"
        : "=r"(ok) : "r"(bar), "r"(parity) : "memory");
    return __all_sync(0xffffffffu, ok);
}
__device__ __forceinline__ void mbar_wait_u(uint32_t bar, uint32_t parity) {
    for (uint32_t it = 0; !mbar_try(bar, parity); it++)
        if (it > kSpinLimit) __trap();
}
__device__ __forceinline__ void tma3d(uint32_t dst, const CUtensorMap* tm, int c0, int c1, int c2, uint32_t bar, uint64_t pol) {
    asm volatile(
        "cp.async.bulk.tensor.3d.shared::cluster.global.mbarrier::complete_tx::bytes.L2::cache_hint "
        "[%0], [%1, {%2, %3, %4}], [%5], %6;"
        ::"r"(dst), "l"(tm), "r"(c0), "r"(c1), "r"(c2), "r"(bar), "l"(pol) : "memory");
}
__device__ __forceinline__ void tma3d_prefetch(const CUtensorMap* tm, int c0, int c1, int c2, uint64_t pol) {
    asm volatile("cp.async.bulk.prefetch.tensor.3d.L2.global.L2::cache_hint [%0, {%1, %2, %3}], %4;"
                 ::"l"(tm), "r"(c0), "r"(c1), "r"(c2), "l"(pol) : "memory");
}
__device__ __forceinline__ uint64_t make_policy(bool keep) {
    uint64_t pol;
    if (keep) asm volatile("createpolicy.fractional.L2::evict_normal.b64 %0, 1.0;" : "=l"(pol));
    else      asm volatile("createpolicy.fractional.L2::evict_first.b64 %0, 1.0;" : "=l"(pol));
    return pol;
}
__device__ __forceinline__ void ldsm4(uint32_t (&r)[4], uint32_t addr) {
    asm volatile("ldmatrix.sync.aligned.m8n8.x4.shared.b16 {%0,%1,%2,%3}, [%4];"
                 : "=r"(r[0]), "=r"(r[1]), "=r"(r[2]), "=r"(r[3]) : "r"(addr) : "memory");
}
__device__ __forceinline__ void ldsm4t(uint32_t (&r)[4], uint32_t addr) {
    asm volatile("ldmatrix.sync.aligned.m8n8.x4.trans.shared.b16 {%0,%1,%2,%3}, [%4];"
                 : "=r"(r[0]), "=r"(r[1]), "=r"(r[2]), "=r"(r[3]) : "r"(addr) : "memory");
}
__device__ __forceinline__ void mma16816(float (&c)[4], const uint32_t (&a)[4], uint32_t b0, uint32_t b1) {
    asm volatile("mma.sync.aligned.m16n8k16.row.col.f32.bf16.bf16.f32 {%0,%1,%2,%3}, {%4,%5,%6,%7}, {%8,%9}, {%0,%1,%2,%3};"
                 : "+f"(c[0]), "+f"(c[1]), "+f"(c[2]), "+f"(c[3])
                 : "r"(a[0]), "r"(a[1]), "r"(a[2]), "r"(a[3]), "r"(b0), "r"(b1));
}
__device__ __forceinline__ float bf16r(float v) { return __bfloat162float(__float2bfloat16_rn(v)); }
__device__ __forceinline__ uint32_t pack_bf16(float lo, float hi) {
    uint32_t r;
    asm("cvt.rn.bf16x2.f32 %0, %1, %2;" : "=r"(r) : "f"(hi), "f"(lo));
    return r;
}
__device__ __forceinline__ bool elect() {
    uint32_t p;
    asm volatile("{\n\t.reg .pred e;\n\telect.sync _|e, 0xffffffff;\n\tselp.u32 %0, 1, 0, e;\n\t}" : "=r"(p));
    return p;
}
__device__ __forceinline__ float fast_sqrt(float v) {
    float r;
    asm("sqrt.approx.f32 %0, %1;" : "=f"(r) : "f"(v));
    return r;
}
__device__ __forceinline__ float ex2(float v) {
    float r;
    asm("ex2.approx.ftz.f32 %0, %1;" : "=f"(r) : "f"(v));
    return r;
}
__device__ __forceinline__ void st_packet(uint4* p, uint32_t a, uint32_t b, uint32_t c, uint32_t tag) {
    asm volatile(
        "{\n\t.reg .b64 lo, hi;\n\t.reg .b128 v;\n\t"
        "mov.b64 lo, {%1, %2};\n\tmov.b64 hi, {%3, %4};\n\tmov.b128 v, {lo, hi};\n\t"
        "st.relaxed.gpu.global.b128 [%0], v;\n\t}"
        ::"l"(p), "r"(a), "r"(b), "r"(c), "r"(tag) : "memory");
}
__device__ __forceinline__ void st_packet(uint4* p, float a, float b, float c, uint32_t tag) {
    st_packet(p, __float_as_uint(a), __float_as_uint(b), __float_as_uint(c), tag);
}
__device__ __forceinline__ uint4 ld_packet(const uint4* p) {
    uint4 v;
    asm volatile(
        "{\n\t.reg .b64 lo, hi;\n\t.reg .b128 v;\n\t"
        "ld.relaxed.gpu.global.b128 v, [%4];\n\t"
        "mov.b128 {lo, hi}, v;\n\tmov.b64 {%0, %1}, lo;\n\tmov.b64 {%2, %3}, hi;\n\t}"
        : "=r"(v.x), "=r"(v.y), "=r"(v.z), "=r"(v.w) : "l"(p) : "memory");
    return v;
}
__device__ __forceinline__ void red_packet(float4* p, float a, float b, float c) {
    asm volatile("red.relaxed.gpu.global.add.v4.f32 [%0], {%1, %2, %3, %4};"
                 ::"l"(p), "f"(a), "f"(b), "f"(c), "f"(1.f) : "memory");
}
#define POLL_UNTIL(pause, loads, done)            \
    for (uint32_t it_ = 0;; it_++) {              \
        loads;                                    \
        if (__all_sync(0xffffffffu, done)) break; \
        if (it_ > kSpinLimit) __trap();           \
        if (pause) __nanosleep(pause);            \
    }
__device__ __forceinline__ uint32_t round24(float v) {
    const uint32_t u = __float_as_uint(v);
    return u + ((u & 0x7f800000u) == 0x7f800000u ? 0u : 0x80u);
}
__device__ __forceinline__ void st_packet5(uint4* p, const float* v, uint32_t tag) {
    const uint32_t r0 = round24(v[0]), r1 = round24(v[1]), r2 = round24(v[2]), r3 = round24(v[3]), r4 = round24(v[4]);
    st_packet(p, __byte_perm(r0, r1, 0x5321), __byte_perm(r1, r2, 0x6532), __byte_perm(r2, r3, 0x7653),
              (r4 >> 8) | (tag << 24));
}
__device__ __forceinline__ void add_packet5(float (&a)[5], const uint4& v) {
    a[0] += __uint_as_float(v.x << 8);
    a[1] += __uint_as_float(__funnelshift_r(v.x, v.y, 16) & 0xffffff00u);
    a[2] += __uint_as_float(__funnelshift_r(v.y, v.z, 8) & 0xffffff00u);
    a[3] += __uint_as_float(v.z & 0xffffff00u);
    a[4] += __uint_as_float(v.w << 8);
}
__device__ __forceinline__ uint32_t now_ns() {
    uint32_t t;
    asm volatile("mov.u32 %0, %globaltimer_lo;" : "=r"(t));
    return t;
}
__device__ __forceinline__ int fresh_lane() {
    int lane = threadIdx.x & 31;
    asm volatile("" : "+r"(lane));
    return lane;
}
__device__ __forceinline__ void pause_ns(uint32_t ns) {
    const uint32_t t0 = now_ns();
    while (now_ns() - t0 < ns) __nanosleep(100);
}
__device__ __forceinline__ float bf_lo(uint32_t v) { return __uint_as_float(v << 16); }
__device__ __forceinline__ float bf_hi(uint32_t v) { return __uint_as_float(v & 0xffff0000u); }
__device__ __forceinline__ float warp_sum(float v) {
#pragma unroll
    for (int o = 16; o > 0; o >>= 1) v += __shfl_xor_sync(0xffffffffu, v, o);
    return v;
}

constexpr float kScale = 0.07216878364870322f, kLog2e = 1.4426950408889634f;
__device__ __forceinline__ float score(float dot, bool round) {
    return round ? bf16r(bf16r(dot) * kScale) * kLog2e : dot * (kScale * kLog2e);
}

struct Attn {
    float m, l;
    float acc[3][4];
};

__device__ __forceinline__ uint32_t probability(Attn& st, float s) {
    const float e = ex2(s - st.m);
    st.l += e;
    const float hi = bf16r(e);
    const uint32_t hl = pack_bf16(hi, e - hi);
    uint32_t pv;
    asm volatile("movmatrix.sync.aligned.m8n8.trans.b16 %0, %1;" : "=r"(pv) : "r"(hl));
    return pv;
}

__device__ __forceinline__ uint32_t softmax_step(Attn& st, float s) {
    if (__any_sync(0xffffffffu, s > st.m)) {
        float mx = fmaxf(s, __shfl_xor_sync(0xffffffffu, s, 4));
        mx = fmaxf(mx, __shfl_xor_sync(0xffffffffu, mx, 8));
        mx = fmaxf(mx, __shfl_xor_sync(0xffffffffu, mx, 16));
        mx = fmaxf(mx, st.m);
        const float corr = ex2(st.m - mx);
        st.m = mx;
        st.l *= corr;
#pragma unroll
        for (int a = 0; a < 3; a++)
#pragma unroll
            for (int i = 0; i < 4; i++) st.acc[a][i] *= corr;
    }
    return probability(st, s);
}

__global__ void __launch_bounds__(kThreads, 1)
fused_decode_kernel(const __grid_constant__ Params P) {
    extern __shared__ __align__(1024) unsigned char smem[];
    const uint32_t sbase = (uint32_t)__cvta_generic_to_shared(smem);
    const uint32_t sync0 = sbase + kOffSync;
    float* const wbuf = reinterpret_cast<float*>(smem + kOffWbuf);

    const int lane = threadIdx.x & 31;
    const int w = __shfl_sync(0xffffffffu, threadIdx.x >> 5, 0);
    const int cta = blockIdx.x;
    const int h = cta >> 2, jq = cta & 3;

    if (w >= 10) {
        const int i0 = 80 * (w - 10) + lane;
#pragma unroll
        for (int i = 0; i < 3; i++)
            if (i < 2 || lane < 16)
                asm volatile("cp.async.cg.shared.global [%0], [%1], 16;"
                             ::"r"(sbase + kOffWbuf + 16 * (i0 + 32 * i)), "l"(reinterpret_cast<const uint4*>(P.x) + i0 + 32 * i) : "memory");
    }
    if (elect()) {
        if (w == 8) {
#pragma unroll
            for (int i = 0; i < kSlots; i++) {
                mbar_init(sbase + kOffFull + 8 * i, 1);
                mbar_init(sbase + kOffEmpty + 8 * i, 8);
            }
        } else if (w == 9) {
            asm volatile("cp.async.bulk.prefetch.L2.global.L2::cache_hint [%0], %1, %2;"
                         ::"l"(P.kA + (size_t)((32 + h) * 4096 + 3072 + 256 * jq) * 192), "r"(8 * kSlotBytes),
                           "l"(make_policy(false)) : "memory");
#pragma unroll
            for (int i = 0; i < 10; i++) asm volatile("prefetch.tensormap [%0];" ::"l"(&P.tm[(i + 4) % 10]) : "memory");
        } else if (w == 10) {
#pragma unroll
            for (int i = 0; i < 14; i++) mbar_init(sync0 + 8 * i, (8 * i == kBarRows || 8 * i >= kBarSentY) ? 8 : 1);
        }
        if (w != 9) asm volatile("fence.mbarrier_init.release.cluster;" ::: "memory");
    }
    __syncwarp();
    if (w == 8) {
        asm volatile("bar.arrive 1, %0;" ::"n"(kThreads) : "memory");
    } else {
        asm volatile("bar.sync 1, %0;" ::"n"(kThreads) : "memory");
    }

    if (w < 8) {
        asm volatile("setmaxnreg.inc.sync.aligned.u32 232;");
        const uint32_t full0 = sbase + kOffFull;
        const uint32_t frag0 = sbase + w * 1024 + (lane & 7) * 128 + (((lane >> 3) ^ (lane & 7)) << 4), frag1 = frag0 ^ 64;
        auto frag_addr = [&](uint32_t s, int k) { return ((k & 1) ? frag1 : frag0) + s * (8 * kSlotBytes) + (k >> 1) * 8192; };
        uint32_t par = 0, rpos = 0, nrows = 0;
        auto wait_tile = [&](uint32_t s) { mbar_wait(full0 + 8 * s, (par >> s) & 1u); };
        auto tile_ready = [&](uint32_t s) { return mbar_test(full0 + 8 * s, (par >> s) & 1u); };
        auto release = [&](uint32_t s) {
            par ^= 1u << s;
            __syncwarp();
            if (elect()) mbar_arrive(full0 + 8 * s + (kOffEmpty - kOffFull));
        };
        auto ring_release = [&]() {
            release(rpos);
            if (++rpos == kRing) rpos = 0;
        };
        auto row_acquire = [&]() { mbar_wait(sync0 + kBarFree, (nrows & 1) ^ 1); };
        auto row_publish = [&]() {
            __syncwarp();
            if (elect()) mbar_arrive(sync0 + kBarRows);
            nrows++;
        };

        uint32_t rf[8][6][4];
#pragma unroll
        for (int i = 0; i < 8; i++)
#pragma unroll
            for (int s = 0; s < 6; s++)
#pragma unroll
                for (int k = 0; k < 4; k++) rf[i][s][k] = 0;

#pragma unroll 1
        for (int pc = 0;; pc++) {
            const uint32_t op = P.prog[pc];
            const uint32_t kind = op & 7u;
            if (kind == OP_END) break;
            const int lane = fresh_lane();
            const int g = lane >> 2, t = lane & 3;
            float* const row = wbuf + w * kWRow;

            if (kind == OP_SEG) {
                const uint32_t b = (op >> 3) & 1u;
                mbar_wait(sync0 + kBarQ + 8 * b, (op >> 4) & 1u);
                const uint2* qf = reinterpret_cast<const uint2*>(smem + kOffQf) + b * 48 + (lane & 7);
                Attn st;
                st.m = -INFINITY; st.l = 0.f;
#pragma unroll
                for (int a = 0; a < 3; a++)
#pragma unroll
                    for (int i = 0; i < 4; i++) st.acc[a][i] = 0.f;

                if (op & (1u << 7)) {
                    float c[4][4] = {};
#pragma unroll
                    for (int k = 0; k < 6; k++) {
                        const uint2 q = qf[8 * k];
#pragma unroll
                        for (int i = 0; i < 4; i++) mma16816(c[i], rf[2 * i][k], q.x, q.y);
                    }
                    float sc[4];
#pragma unroll
                    for (int i = 0; i < 4; i++) sc[i] = score(c[i][0] + c[i][3], op & 32u);
                    float mx = fmaxf(fmaxf(sc[0], sc[1]), fmaxf(sc[2], sc[3]));
                    mx = fmaxf(mx, __shfl_xor_sync(0xffffffffu, mx, 4));
                    mx = fmaxf(mx, __shfl_xor_sync(0xffffffffu, mx, 8));
                    st.m = fmaxf(mx, __shfl_xor_sync(0xffffffffu, mx, 16));
                    uint32_t pv[4];
#pragma unroll
                    for (int i = 0; i < 4; i++) pv[i] = probability(st, sc[i]);
#pragma unroll
                    for (int i = 0; i < 4; i++)
#pragma unroll
                        for (int k = 0; k < 6; k++)
                            mma16816(st.acc[k >> 1], rf[2 * i + 1][k], (g >> 1) == 2 * (k & 1) ? pv[i] : 0u,
                                     (g >> 1) == 2 * (k & 1) + 1 ? pv[i] : 0u);
                }

                uint32_t lo = P.prog[pc + 1], hi = P.prog[pc + 2];
                pc += 2;
                bool haveK = false;
#pragma unroll 1
                while (lo & 15u) {
                    const bool rel = lo & 4u;
                    uint32_t sK = kRing - 2 + 2 * (lo & 3u), sV = sK + 1;
                    if (!(lo & 3u)) {
                        sK = rpos;
                        sV = rpos == kRing - 1 ? 0 : rpos + 1;
                        rpos = sV == kRing - 1 ? 0 : sV + 1;
                    }
                    lo = __funnelshift_r(lo, hi, 4);
                    hi >>= 4;
                    if (!haveK) wait_tile(sK);
                    const bool haveV = tile_ready(sV);
                    float c[2][4] = {};
#pragma unroll
                    for (int k = 0; k < 6; k++) {
                        uint32_t a[4];
                        ldsm4(a, frag_addr(sK, k));
                        const uint2 q = qf[8 * k];
                        mma16816(c[k & 1], a, q.x, q.y);
                    }
                    if (rel) release(sK);
                    const uint32_t pv = softmax_step(st, score((c[0][0] + c[0][3]) + (c[1][0] + c[1][3]), op & 32u));
                    if (!haveV) wait_tile(sV);
                    haveK = tile_ready((lo & 3u) ? kRing - 2 + 2 * (lo & 3u) : rpos);
#pragma unroll
                    for (int k = 0; k < 6; k++) {
                        uint32_t a[4];
                        ldsm4t(a, frag_addr(sV, k));
                        mma16816(st.acc[k >> 1], a, (g >> 1) == 2 * (k & 1) ? pv : 0u, (g >> 1) == 2 * (k & 1) + 1 ? pv : 0u);
                    }
                    if (rel) release(sV);
                }

                float l = st.l;
                l += __shfl_xor_sync(0xffffffffu, l, 4);
                l += __shfl_xor_sync(0xffffffffu, l, 8);
                l += __shfl_xor_sync(0xffffffffu, l, 16);
                row_acquire();
#pragma unroll
                for (int a = 0; a < 3; a++) {
                    row[64 * a + 16 * t + g] = st.acc[a][0] + st.acc[a][1];
                    row[64 * a + 16 * t + g + 8] = st.acc[a][2] + st.acc[a][3];
                }
                if (lane == 0) { wbuf[8 * kWRow + w] = st.m; wbuf[8 * kWRow + 8 + w] = l; }
                row_publish();
            } else if (kind == OP_RFLOAD) {
#pragma unroll 1
                for (uint32_t tile = (op >> 3) & 7u; tile < (op >> 6); tile++) {
                    wait_tile(rpos);
#pragma unroll
                    for (int i = 0; i < 8; i++) {
                        if (tile == i) {
#pragma unroll
                            for (int k = 0; k < 6; k++) {
                                if (i & 1) ldsm4t(rf[i][k], frag_addr(rpos, k));
                                else ldsm4(rf[i][k], frag_addr(rpos, k));
                            }
                        }
                    }
                    ring_release();
                }
            } else if (kind == OP_QPROJ) {
                const uint32_t mask = (op >> 3) & 3u;
#pragma unroll 1
                for (uint32_t b = 0; b < 2; b++)
                    if ((mask >> b) & 1u) mbar_wait(sync0 + kBarXn + 8 * b, (op >> 5) & 1u);
                const uint32_t bb = mask == 3u ? (g & 1) : (mask >> 1);
                const uint32_t* xs = reinterpret_cast<const uint32_t*>(smem + kOffXn) + bb * 80 + 4 * w + t;
                float acc[3][4] = {};
#pragma unroll 1
                for (int p = 0; p < 3; p++) {
                    wait_tile(rpos);
                    if (p < 2 || w < 4) {
                        const uint32_t xv = xs[32 * p];
                        const uint32_t shrink = p == 2 ? 4096 : 0;
#pragma unroll
                        for (int k = 0; k < 6; k++) {
                            uint32_t a[4];
                            ldsm4t(a, frag_addr(rpos, k) - (k >> 1) * shrink);
                            mma16816(acc[k >> 1], a, (g >> 1) == 2 * (k & 1) ? xv : 0u, (g >> 1) == 2 * (k & 1) + 1 ? xv : 0u);
                        }
                    }
                    ring_release();
                }
#pragma unroll 1
                for (uint32_t b = 0; b < 2; b++) {
                    if (!((mask >> b) & 1u)) continue;
                    row_acquire();
#pragma unroll
                    for (int a = 0; a < 3; a++) {
                        row[64 * a + 16 * t + g] = b ? acc[a][1] : acc[a][0];
                        row[64 * a + 16 * t + g + 8] = b ? acc[a][3] : acc[a][2];
                    }
                    row_publish();
                }
            } else {
                const uint32_t mask = (op >> 3) & 3u;
                const uint32_t bb = mask == 3u ? (g & 1) : (mask >> 1);
                const uint32_t* ob = reinterpret_cast<const uint32_t*>(smem + kOffObf) + bb * 24 + t;
                const uint32_t roff = ((lane & 7) + 8 * (lane >> 4)) * 128 + ((((lane >> 3) & 1) ^ (lane & 7)) << 4);
                uint32_t sl[3];
#pragma unroll
                for (int p = 0; p < 3; p++) {
                    sl[p] = rpos;
                    if (++rpos == kRing) rpos = 0;
                }
                auto frag = [&](uint32_t (&a)[4], int p, int mt) {
                    ldsm4t(a, ((sbase + sl[p] * 8 * kSlotBytes + roff) ^ (((5 * w + mt) & 3) << 5)) + ((5 * w + mt) >> 2) * 2048);
                };
                uint32_t a0[5][4];
                wait_tile(sl[0]);
#pragma unroll
                for (int mt = 0; mt < 5; mt++) frag(a0[mt], 0, mt);
                release(sl[0]);
                wait_tile(sl[1]);
                wait_tile(sl[2]);
                row_acquire();
                if (mask & 1u) mbar_wait(sync0 + kBarO, (op >> 5) & 1u);
                if (mask & 2u) mbar_wait(sync0 + kBarO + 8, (op >> 5) & 1u);
                float c[3][4] = {};
#pragma unroll
                for (int p = 0; p < 3; p++) {
                    const uint32_t b0 = ob[8 * p], b1 = ob[8 * p + 4];
#pragma unroll
                    for (int mt = 0; mt < 5; mt++) {
                        if (p > 0) frag(a0[mt], p, mt);
                        const bool on = (g >> 1) == (mt & 3);
                        mma16816(c[mt == 4 ? 2 : (mt & 1)], a0[mt], on ? b0 : 0u, on ? b1 : 0u);
                    }
                    if (p > 0) release(sl[p]);
                }
                row[16 * t + g] = c[0][0] + c[1][0]; row[80 + 16 * t + g] = c[0][1] + c[1][1];
                row[16 * t + g + 8] = c[0][2] + c[1][2]; row[80 + 16 * t + g + 8] = c[0][3] + c[1][3];
                if (t == 0) {
                    row[64 + g] = c[2][0]; row[144 + g] = c[2][1];
                    row[72 + g] = c[2][2]; row[152 + g] = c[2][3];
                }
                __syncwarp();
                if (lane < 27) {
                    const bool last = ((op >> 5) & 3u) == 3u;
                    float4* dst = (last ? g_out[0][cta % kOutReplicas] : g_acc[0][(op >> 5) & 3u]) + (27 * w + lane) * kAccPad;
                    const float* y = row + 3 * lane;
                    if (mask & 1u) red_packet(dst, y[0], y[1], lane < 26 ? y[2] : 0.f);
                    if (mask & 2u) red_packet(dst + (last ? kOutReplicas : 3) * kAccPad * kAccPackets, y[80], y[81], lane < 26 ? y[82] : 0.f);
                }
                __syncwarp();
                if (lane < 2 && ((mask >> lane) & 1u)) mbar_arrive(sync0 + kBarSentY + 8 * lane);
            }
        }
    } else {
        asm volatile("setmaxnreg.dec.sync.aligned.u32 40;");
        if (w == 8) {
            if (elect()) {
#pragma unroll
                for (int p = 0; p < kRing; p++) {
                    const CUtensorMap* tm = &P.tm[p == 2 ? 8 : 4];
                    mbar_expect(sbase + kOffFull + 8 * p, p == 2 ? 4 * kSlotBytes : 8 * kSlotBytes);
                    tma3d(sbase + p * 8 * kSlotBytes, tm, 0, 160 * jq + 64 * p, 3 * h, sbase + kOffFull + 8 * p, make_policy(false));
                    tma3d_prefetch(tm, 0, 160 * jq + 64 * p, 3 * h, make_policy(true));
                }
            }
            __syncwarp();
            const int rowA = h * 4096 + 3072 + 256 * jq, rowB = h * 4096 + 1024 * jq;
            const int rowWq = 160 * jq, rowWo = 192 * h + 48 * jq;
            const uint64_t polKeep = make_policy(true), polStream = make_policy(false);
            const uint32_t rot = 64u * 11u * ((h & 3) + ((h >> 2) & 3) + (h >> 4));
            auto coord = [&](uint32_t e) {
                const uint32_t off = (e >> 10) & 0x3ffffu;
                const uint32_t offB = (off & ~0x3ffu) + ((off + rot) & 0x3c0u) + rowB;
                return (int)((e & 4u) ? off + ((e & 2u) ? rowWo : rowWq) : ((e & 2u) ? offB : off + rowA));
            };
            auto line = [&](uint32_t e) { return (e & 6u) == 4u ? 3 * h : 0; };
            auto map = [&](uint32_t e) { return &P.tm[(e & 7u) + ((e >> 26) & 4u)]; };
            auto interval = [&](uint32_t e) {
                return (e & 6u) == 6u ? kTauWo : ((e & LD_HANDOFF) ? kTauHandoff : kTau) >> ((e >> 28) & 1u);
            };
            uint32_t par = 7u, recent = 0xf012u, latest = 2, m = kRing + 1, na = 0, credit = kCredit, next = now_ns() + kStartDelay;
            auto landed = [&](uint32_t s) { return mbar_test(sbase + kOffFull + 8 * s, ((par >> s) & 1u) ^ 1u); };
            uint32_t e = P.loads[kRing];
            int c1 = coord(e);
#pragma unroll 1
            for (uint32_t n = kRing; e & LD_VALID; n++) {
                const uint32_t s = (e >> 4) & 15u;
                const uint32_t full = sbase + kOffFull + 8 * s;
                const uint32_t enext = P.loads[n + 1];
                if (m < n) m = n;
                for (uint32_t it = 0; !mbar_test(full + (kOffEmpty - kOffFull), ((par >> s) & 1u) ^ 1u); it++) {
                    if (it > 16 * kSpinLimit) __trap();
                    const uint32_t f = P.loads[m];
                    if (m >= n + ((e & LD_FAR) ? kLookFar : kLook) || !(f & LD_VALID)) continue;
                    if (f & LD_HIT) { m++; continue; }
                    const uint32_t now = now_ns();
                    if ((int)(now - next) >= 0 && landed(latest)) {
                        if (elect()) tma3d_prefetch(map(f), 0, coord(f), line(f), polStream);
                        next = now + interval(f);
                        m++;
                    }
                }
                if (e & LD_ANCHOR) {
                    const uint32_t t0 = __shfl_sync(0xffffffffu, *reinterpret_cast<volatile uint32_t*>(smem + kOffAnchor), 0) + P.anchorDelay[na];
                    if (m <= n || (int)(t0 - next) > 0) next = t0;
                    credit = P.anchorCredit[na++];
                }
                const bool fromHbm = !(e & LD_HIT) && m <= n;
                if (fromHbm) {
                    const uint32_t o = (recent >> (4 * kWindow - 4)) & 15u;
                    if (o != s && o != 15u) mbar_wait_u(sbase + kOffFull + 8 * o, ((par >> o) & 1u) ^ 1u);
                    uint32_t now = now_ns();
                    while ((int)(now - next) < 0) now = now_ns();
                    if ((int)(now - credit - next) > 0) next = now - credit;
                    next += interval(e);
                }
                if (elect()) {
                    mbar_expect(full, (e & 6u) == 6u ? 20480 : (8 * kSlotBytes) >> ((e >> 28) & 1u));
                    tma3d(sbase + s * 8 * kSlotBytes, map(e), 0, c1, line(e), full, polStream);
                    if (e & LD_KEEP) tma3d_prefetch(map(e), 0, c1, line(e), polKeep);
                }
                const uint32_t x = recent ^ (s * 0x1111u);
                recent |= (~(((x & 0x7777u) + 0x7777u) | x) & 0x8888u) * 15u >> 3;
                if (fromHbm) {
                    recent = (recent << 4) | s;
                    latest = s;
                }
                par ^= 1u << s;
                e = enext;
                c1 = coord(e);
            }
        } else {
            if (w == 9) {
#pragma unroll 1
                for (int n = 0;; n++) {
                    const uint32_t job = P.merge[n];
                    if ((job & 3u) == MG_END) break;
                    const uint32_t b = (job >> 2) & 1u;
                    const uint32_t tag = 1 + ((job >> 3) & 3u);
                    mbar_wait(sync0 + kBarRows, n & 1);
                    if ((job & 3u) == MG_Q) {
                        float o[5] = {}, e[5] = {};
                        const float* ext = wbuf + 2 * (lane & 3) * kWRow + 5 * min(32 + (lane >> 2), 38);
#pragma unroll
                        for (int k = 0; k < 5; k++) e[k] = ext[k] + ext[kWRow + k];
#pragma unroll
                        for (int i = 0; i < 8; i++)
#pragma unroll
                            for (int k = 0; k < 5; k++) o[k] += wbuf[i * kWRow + 5 * lane + k];
                        st_packet5(&g_q[b][h][jq][lane], o, tag);
#pragma unroll
                        for (int k = 0; k < 5; k++) {
                            e[k] += __shfl_xor_sync(0xffffffffu, e[k], 1);
                            e[k] += __shfl_xor_sync(0xffffffffu, e[k], 2);
                        }
                        if ((lane & 3) == 0) st_packet5(&g_q[b][h][jq][32 + (lane >> 2)], e, tag);
                        __syncwarp();
                        if (lane == 0) mbar_arrive(sync0 + kBarSentQ + 8 * b);
                    } else {
                        float2* cp = reinterpret_cast<float2*>(smem + kOffCpart) + b * (kWRow / 2) + 3 * lane;
                        float2* cml = reinterpret_cast<float2*>(smem + kOffMl + 64) + b;
                        const float4* ml = reinterpret_cast<const float4*>(smem + kOffMl);
                        const bool merge = !(job & 32u);
                        const float2 pml = merge ? *cml : make_float2(-INFINITY, 0.f);
                        const float4 m0 = ml[0], m1 = ml[1];
                        float sc[8] = {m0.x, m0.y, m0.z, m0.w, m1.x, m1.y, m1.z, m1.w};
                        const float M = fmaxf(fmaxf(fmaxf(fmaxf(sc[0], sc[1]), fmaxf(sc[2], sc[3])),
                                                    fmaxf(fmaxf(sc[4], sc[5]), fmaxf(sc[6], sc[7]))), pml.x);
#pragma unroll
                        for (int i = 0; i < 8; i++) sc[i] = ex2(sc[i] - M);
                        const float ps = ex2(pml.x - M);
                        float2 o[3];
#pragma unroll
                        for (int k = 0; k < 3; k++) {
                            o[k] = merge ? cp[k] : make_float2(0.f, 0.f);
                            o[k].x *= ps; o[k].y *= ps;
                        }
#pragma unroll
                        for (int i = 0; i < 8; i++)
#pragma unroll
                            for (int k = 0; k < 3; k++) {
                                const float2 v = reinterpret_cast<const float2*>(wbuf)[i * (kWRow / 2) + 3 * lane + k];
                                o[k].x = fmaf(v.x, sc[i], o[k].x);
                                o[k].y = fmaf(v.y, sc[i], o[k].y);
                            }
                        const float4 l0 = ml[2], l1 = ml[3];
                        const float L = fmaf(pml.y, ps, ((l0.x * sc[0] + l0.y * sc[1]) + (l0.z * sc[2] + l0.w * sc[3])) +
                                                        ((l1.x * sc[4] + l1.y * sc[5]) + (l1.z * sc[6] + l1.w * sc[7])));
                        if (job & 64u) {
                            uint4* dst = &g_p[b][h][lane >> 3][jq][2 * (lane & 7)];
                            st_packet(dst, o[0].x, o[0].y, o[1].x, tag);
                            st_packet(dst + 1, o[1].y, o[2].x, o[2].y, tag);
                            if (lane < 8) st_packet(&g_p[b][h][lane >> 1][jq][16 + (lane & 1)], M, L, 0.f, tag);
                            if (lane == 0) mbar_arrive(sync0 + kBarSentP + 8 * b);
                        } else {
#pragma unroll
                            for (int k = 0; k < 3; k++) cp[k] = o[k];
                            __syncwarp();
                            if (lane == 0) *cml = make_float2(M, L);
                        }
                    }
                    __syncwarp();
                    if (lane == 0) mbar_arrive(sync0 + kBarFree);
                }
            } else {
                const uint32_t b = w - 10;
                __nv_bfloat16* const xn = reinterpret_cast<__nv_bfloat16*>(smem + kOffXn) + b * 160;
                __nv_bfloat16* const qd = reinterpret_cast<__nv_bfloat16*>(smem + kOffQf) + b * 192;
                __nv_bfloat16* const ob = reinterpret_cast<__nv_bfloat16*>(smem + kOffObf) + b * 48;
                uint2* const own = reinterpret_cast<uint2*>(smem + kOffOwn) + 2 * b;
#pragma unroll 1
                for (uint32_t layer = 0; layer < 4; layer++) {
                    const uint32_t tag = layer + 1;
                    {
                        int lane = fresh_lane();
                        uint32_t x01[7], x2[7];
                        if (layer == 0) {
                            const uint4* stage = reinterpret_cast<const uint4*>(wbuf) + 80 * b;
                            asm volatile("cp.async.wait_all;" ::: "memory");
                            __syncwarp();
#pragma unroll
                            for (int i = 0; i < 7; i++) {
                                const int p = lane + 32 * i, u = p % 27;
                                const unsigned short* xp = reinterpret_cast<const unsigned short*>(stage) + (p / 27) * 80 + 3 * u;
                                x01[i] = p < kAccPackets ? xp[0] | ((uint32_t)xp[1] << 16) : 0u;
                                x2[i] = (p < kAccPackets && u < 26) ? xp[2] : 0u;
                            }
                        } else {
                            mbar_wait(sync0 + kBarSentY + 8 * b, (layer - 1) & 1);
                            pause_ns(kDelayX);
                            uint4 v[7];
                            const uint4* src = reinterpret_cast<const uint4*>(&g_acc[b][layer - 1][lane * kAccPad]);
                            const uint32_t done = __float_as_uint(kAccDone);
                            POLL_UNTIL(kPauseX, v[0] = ld_packet(src + (27 * (cta & 7) + min(lane, 26) - lane) * kAccPad), v[0].w == done);
                            POLL_UNTIL(kPauseX,
                                v[0] = ld_packet(src); v[1] = ld_packet(src + 32 * kAccPad); v[2] = ld_packet(src + 64 * kAccPad);
                                v[3] = ld_packet(src + 96 * kAccPad); v[4] = ld_packet(src + 128 * kAccPad);
                                v[5] = ld_packet(src + 160 * kAccPad); v[6] = ld_packet(src + (lane < 24 ? 192 * kAccPad : 0)),
                                v[0].w == done && v[1].w == done && v[2].w == done && v[3].w == done && v[4].w == done &&
                                    v[5].w == done && v[6].w == done);
#pragma unroll
                            for (int i = 0; i < 7; i++) {
                                x01[i] = pack_bf16(__uint_as_float(v[i].x), __uint_as_float(v[i].y));
                                x2[i] = pack_bf16(__uint_as_float(v[i].z), 0.f);
                            }
                            if (lane >= 24) x01[6] = x2[6] = 0u;
                        }
#pragma unroll
                        for (int i = 0; i < 7; i++) {
                            const int p = lane + 32 * i;
                            if ((p & 127) == cta && p < kAccPackets) {
                                own[i >> 2] = make_uint2(x01[i], x2[i]);
                            }
                        }
                        float sum = 0.f;
#pragma unroll
                        for (int i = 0; i < 7; i++) sum += (bf_lo(x01[i]) + bf_hi(x01[i])) + bf_lo(x2[i]);
                        const float mean = warp_sum(sum) * (1.f / 640.f);
                        float sq = 0.f;
#pragma unroll
                        for (int i = 0; i < 7; i++) {
                            const bool none = i == 6 && lane >= 24;
                            const float d0 = none ? 0.f : bf_lo(x01[i]) - mean, d1 = none ? 0.f : bf_hi(x01[i]) - mean;
                            const bool last = lane == 26 - 5 * i || lane == 53 - 5 * i;
                            const float d2 = (none || last) ? 0.f : bf_lo(x2[i]) - mean;
                            sq += fmaf(d0, d0, fmaf(d1, d1, d2 * d2));
                        }
                        const float var = warp_sum(sq) * (1.f / 640.f);
                        const float meanb = bf16r(mean);
                        const float rden = __fdividef(1.f, bf16r(fast_sqrt(bf16r(bf16r(var) + 1e-5f))));
#pragma unroll
                        for (int i = 0; i < 7; i++) {
                            const uint32_t q = lane + 32 * i - 54 * jq;
                            if (q < 54u) {
                                const int c = 3 * q - (q >= 27u);
                                xn[c] = __float2bfloat16_rn(bf16r(bf_lo(x01[i]) - meanb) * rden);
                                xn[c + 1] = __float2bfloat16_rn(bf16r(bf_hi(x01[i]) - meanb) * rden);
                                if (q != 26u && q != 53u) xn[c + 2] = __float2bfloat16_rn(bf16r(bf_lo(x2[i]) - meanb) * rden);
                            }
                        }
                        if (lane == 0) *reinterpret_cast<volatile uint32_t*>(smem + kOffAnchor) = now_ns();
                        __syncwarp();
                        if (lane == 0) mbar_arrive(sync0 + kBarXn + 8 * b);
                        if (layer >= 2 && lane < 4 && cta + 128 * (lane >> 1) < kAccPackets)
                            g_acc[b][layer - 2][(cta + 128 * (lane >> 1)) * kAccPad + (lane & 1)] = make_float4(0.f, 0.f, 0.f, 0.f);
                        __syncwarp();
                    }
                    {
                        const int lane = fresh_lane();
                        mbar_wait(sync0 + kBarSentQ + 8 * b, layer & 1);
                        if (layer == 0 || (layer == 1 && b == 1)) pause_ns(kDelayIdle);
                        uint4 v[5];
                        const uint4* src = &g_q[b][h][0][lane];
                        const uint4* ext = &g_q[b][h][lane & 3][lane < 28 ? 32 + (lane >> 2) : 38];
                        POLL_UNTIL(0,
                            v[0] = ld_packet(src); v[1] = ld_packet(src + 40); v[2] = ld_packet(src + 80);
                            v[3] = ld_packet(src + 120); v[4] = ld_packet(ext),
                            (v[0].w >> 24) == tag && (v[1].w >> 24) == tag && (v[2].w >> 24) == tag &&
                                (v[3].w >> 24) == tag && (v[4].w >> 24) == tag);
                        __syncwarp();
                        auto store_q = [&](int d, float q) {
                            qd[(d & ~31) + ((d >> 3) & 1) * 16 + ((d >> 1) & 3) * 4 + ((d >> 4) & 1) * 2 + (d & 1)] =
                                __float2bfloat16_rn(q);
                        };
                        float a[5] = {};
#pragma unroll
                        for (int i = 0; i < 4; i++) add_packet5(a, v[i]);
#pragma unroll
                        for (int k = 0; k < 5; k++) store_q(5 * lane + k, a[k]);
                        float e[5] = {};
                        add_packet5(e, v[4]);
#pragma unroll
                        for (int k = 0; k < 5; k++) {
                            e[k] += __shfl_xor_sync(0xffffffffu, e[k], 1);
                            e[k] += __shfl_xor_sync(0xffffffffu, e[k], 2);
                            const int d = 160 + 5 * (lane >> 2) + k;
                            if ((lane & 3) == 0 && d < 192) store_q(d, e[k]);
                        }
                        __syncwarp();
                        if (lane == 0) mbar_arrive(sync0 + kBarQ + 8 * b);
                    }
                    {
                        const int lane = fresh_lane();
                        mbar_wait(sync0 + kBarSentP + 8 * b, layer & 1);
                        pause_ns((b == 0 && (layer == 0 || layer == 3)) ? kDelayIdle : (layer == 3 ? 0 : kDelayP));
                        uint4 v0, v1, ml;
                        const uint4* src = &g_p[b][h][jq][2 * (lane >> 4)][lane & 15];
                        const uint4* mls = &g_p[b][h][jq][lane & 3][16];
                        POLL_UNTIL(0, v0 = ld_packet(src); v1 = ld_packet(src + 18); ml = ld_packet(mls),
                                   v0.w == tag && v1.w == tag && ml.w == tag);
                        __syncwarp();
                        const float mi = __uint_as_float(ml.x);
                        float M = fmaxf(mi, __shfl_xor_sync(0xffffffffu, mi, 1));
                        M = fmaxf(M, __shfl_xor_sync(0xffffffffu, M, 2));
                        const float sc = ex2(mi - M);
                        float L = __uint_as_float(ml.y) * sc;
                        L += __shfl_xor_sync(0xffffffffu, L, 1);
                        L += __shfl_xor_sync(0xffffffffu, L, 2);
                        const float s0 = __shfl_sync(0xffffffffu, sc, 2 * (lane >> 4));
                        const float s1 = __shfl_sync(0xffffffffu, sc, 2 * (lane >> 4) + 1);
                        float o0 = fmaf(__uint_as_float(v0.x), s0, __uint_as_float(v1.x) * s1);
                        float o1 = fmaf(__uint_as_float(v0.y), s0, __uint_as_float(v1.y) * s1);
                        float o2 = fmaf(__uint_as_float(v0.z), s0, __uint_as_float(v1.z) * s1);
                        o0 += __shfl_xor_sync(0xffffffffu, o0, 16);
                        o1 += __shfl_xor_sync(0xffffffffu, o1, 16);
                        o2 += __shfl_xor_sync(0xffffffffu, o2, 16);
                        if (lane < 16) {
                            ob[3 * lane] = __float2bfloat16_rn(__fdividef(o0, L));
                            ob[3 * lane + 1] = __float2bfloat16_rn(__fdividef(o1, L));
                            ob[3 * lane + 2] = __float2bfloat16_rn(__fdividef(o2, L));
                        }
                        __syncwarp();
                        if (lane == 0) mbar_arrive(sync0 + kBarO + 8 * b);
                        const int p = cta + 128 * lane;
                        if (p < kAccPackets) {
                            const uint2 v = own[lane];
                            red_packet((layer == 3 ? g_out[b][0] : g_acc[b][layer]) + p * kAccPad, bf_lo(v.x), bf_hi(v.x), bf_lo(v.y));
                        }
                    }
                }
                {
                    mbar_wait(sync0 + kBarSentY + 8 * b, 1);
                    const int p = cta + 128 * ((lane / kOutReplicas) & 1), r = lane % kOutReplicas;
                    float4* src = &g_out[b][r][(p < kAccPackets ? p : cta) * kAccPad];
                    const float want = kCtas / kOutReplicas + (r == 0);
                    uint4 v;
                    for (uint32_t it = 0;; it++) {
                        v = ld_packet(reinterpret_cast<const uint4*>(src));
                        if (__all_sync(0xffffffffu, v.w == __float_as_uint(want))) break;
                        if (it > kSpinLimit) __trap();
                    }
                    float o0 = __uint_as_float(v.x), o1 = __uint_as_float(v.y), o2 = __uint_as_float(v.z);
#pragma unroll
                    for (int o = 1; o < kOutReplicas; o <<= 1) {
                        o0 += __shfl_xor_sync(0xffffffffu, o0, o);
                        o1 += __shfl_xor_sync(0xffffffffu, o1, o);
                        o2 += __shfl_xor_sync(0xffffffffu, o2, o);
                    }
                    if (lane < 2 * kOutReplicas && p < kAccPackets) {
                        if (r < 3 - (p % 27 == 26))
                            P.out[b * 640 + (p / 27) * 80 + 3 * (p % 27) + r] = __float2bfloat16_rn(r == 0 ? o0 : r == 1 ? o1 : o2);
                        *src = make_float4(0.f, 0.f, 0.f, 0.f);
                        if (r == 0) g_acc[b][2][p * kAccPad] = make_float4(0.f, 0.f, 0.f, 0.f);
                    }
                }
            }
        }
    }
}


struct Sched {
    Params& P;
    int np = 0, nm = 0, nl = 0, rslot = 0, mark = 0;
    uint32_t pending = 0;
    enum { RF = 1 << 7, FIRST = 1 << 11, PUB = 1 << 12 };

    void handoff_begin() { mark = nl; }
    void handoff_end() { for (int i = mark; i < nl; i++) P.loads[i] |= LD_HANDOFF; }
    void slot(uint32_t e, int s) { P.loads[nl++] = e | (s << 4); }
    void ring(uint32_t e) {
        slot(e | pending, rslot);
        pending = 0;
        rslot = (rslot + 1) % kRing;
    }
    static uint32_t tile(int isB, int b, int idx, int v) {
        return LD_VALID | (2 * isB + v) | (uint32_t)(b * 32 * 4096 + 64 * idx) << 10;
    }
    void pair(int isB, int b, int idx, uint32_t fk = 0, uint32_t fv = 0) {
        ring(tile(isB, b, idx, 0) | fk);
        ring(tile(isB, b, idx, 1) | fv);
    }
    void qproj(int mask, int layer, uint32_t f) {
        for (int p = 0; p < 3; p++) ring(LD_VALID | (4 + (layer & 1)) | (64 * p) << 10 | (p == 2 ? LD_HALF : 0u) | f);
        if (layer > 0) pending = LD_ANCHOR;
        P.prog[np++] = OP_QPROJ | (mask << 3) | (layer << 5);
        for (int b = 0; b < 2; b++)
            if ((mask >> b) & 1) P.merge[nm++] = MG_Q | (b << 2) | (layer << 3);
    }
    void oproj(int mask, int layer, uint32_t fLast) {
        for (int p = 0; p < 3; p++) ring(LD_VALID | (6 + (layer & 1)) | (16 * p) << 10 | (p == 2 ? fLast : 0u));
        P.prog[np++] = OP_OPROJ | (mask << 3) | (layer << 5);
    }
    void rfload(int from, int to, int isB, int b, int idx0) {
        for (int i = from; i < to; i++) ring(tile(isB, b, idx0 + i / 2, i & 1));
        P.prog[np++] = OP_RFLOAD | (from << 3) | (to << 6);
    }
    void seg(int b, int layer, uint32_t flags, const char* order) {
        uint64_t list = 0;
        for (int n = 0; order[n]; n++) {
            const char c = order[n];
            uint64_t item = 12;
            if (c >= 'a' && c <= 'c') item = 12 | (c - 'a' + 1);
            if (c >= 'A' && c <= 'C') item = 8 | (c - 'A' + 1);
            list |= item << (4 * n);
        }
        P.prog[np++] = OP_SEG | (b << 3) | ((layer & 1) << 4) | (layer == 0 ? 32 : 0) | (flags & RF);
        P.prog[np++] = (uint32_t)list;
        P.prog[np++] = (uint32_t)(list >> 32);
        P.merge[nm++] = MG_ATTN | (b << 2) | (layer << 3) | ((flags & FIRST) ? 32 : 0) | ((flags & PUB) ? 64 : 0);
    }
};

void build_schedule(Params& P) {
    for (int i = 0; i < kMaxProg; i++) P.prog[i] = OP_END;
    for (int i = 0; i < kMaxMerge; i++) P.merge[i] = MG_END;
    for (int i = 0; i < kMaxLoads; i++) P.loads[i] = 0;
    const uint32_t anchorDelay[kAnchors] = {200, 200, 200, 200, 0};
    const uint32_t anchorCredit[kAnchors] = {kCredit, 2500, 2500, kCredit, 300};
    for (int i = 0; i < kAnchors; i++) {
        P.anchorDelay[i] = anchorDelay[i];
        P.anchorCredit[i] = anchorCredit[i];
    }

    Sched S{P};
    using F = Sched;
    const int keep[2] = {9, 10};
    auto kept = [&](int b, int idx, int v, uint32_t f) { return (2 * (15 - idx) + (1 - v)) < keep[b] ? f : 0u; };
    int nextD[2] = {3, 7}, nextH[2] = {11, 11}, nextK = 11;
    auto fill = [&](int b, int layer, int n, uint32_t flags = 0) {
        for (int i = 0; i < n; i++) S.pair(1, b, nextD[b]++);
        S.seg(b, layer, flags, &"dd"[2 - n]);
    };
    auto mixed = [&](int b, int layer, uint32_t flags, const char* order, int refill0, const int* pos) {
        int tiles = 0, done = 0, dst[6], n = 0;
        for (const char* c = order; *c; c++)
            if (*c >= 'a' && *c <= 'c') { dst[n++] = kRing + 2 * (*c - 'a'); dst[n++] = kRing + 2 * (*c - 'a') + 1; }
        for (const char* c = order; *c; c++) {
            if (*c != 'h' && *c != 'd' && *c != 'k') continue;
            const int idx = *c == 'h' ? nextH[b]++ : *c == 'k' ? nextK++ : nextD[b]++;
            for (int v = 0; v < 2; v++, tiles++) {
                for (; done < n && pos[done] <= tiles; done++) S.slot(F::tile(1, 1, refill0 + done / 2, done & 1) | LD_FAR, dst[done]);
                S.ring(F::tile(1, b, idx, v) | LD_FAR | kept(b, idx, v, *c == 'h' ? LD_HIT : *c == 'k' ? LD_KEEP : 0u));
            }
        }
        S.seg(b, layer, flags, order);
    };

    S.qproj(3, 0, LD_KEEP);
    S.slot(F::tile(0, 1, 0, 0), kRing);
    S.slot(F::tile(0, 1, 0, 1), kRing + 1);
    S.rfload(0, 8, 0, 0, 0);
    S.seg(0, 0, F::RF | F::FIRST | F::PUB, "");
    S.handoff_begin();
    for (int i = 1; i < 4; i++) S.pair(0, 1, i);
    S.seg(1, 0, F::FIRST | F::PUB, "addd");
    S.oproj(3, 0, LD_KEEP);
    for (int i = 0; i < 4; i++) S.slot(F::tile(1, 0, i / 2, i & 1), kRing + i);
    S.qproj(3, 1, LD_KEEP);
    for (int i = 4; i < 6; i++) S.slot(F::tile(1, 0, i / 2, i & 1), kRing + i);
    S.handoff_end();
    for (int i = 3; i < 16; i++) S.pair(1, 0, i, kept(0, i, 0, LD_KEEP), kept(0, i, 1, LD_KEEP));
    S.seg(0, 1, F::FIRST | F::PUB, "dddAdddBdddCdddd");
    S.handoff_begin();
    S.oproj(1, 1, 0);
    fill(1, 1, 2, F::FIRST);
    S.qproj(1, 2, LD_HIT);
    fill(1, 1, 1);
    S.seg(0, 2, F::RF | F::FIRST | F::PUB, "");
    S.rfload(0, 2, 1, 1, 3);
    S.oproj(1, 2, LD_HIT);
    S.rfload(2, 6, 1, 1, 3);
    fill(1, 1, 1);
    S.qproj(1, 3, LD_HIT);
    S.rfload(6, 8, 1, 1, 3);
    S.handoff_end();
    const int pos4[6] = {3, 3, 4, 5, 7, 7};
    mixed(0, 3, F::FIRST, "ahbhchhh", 0, pos4);
    mixed(1, 1, F::RF | F::PUB, "kkABkCkk", 0, nullptr);
    S.handoff_begin();
    S.oproj(2, 1, LD_KEEP);
    fill(0, 3, 2);
    S.qproj(2, 2, 0);
    fill(0, 3, 1);
    for (int i = 0; i < 4; i++) S.pair(0, 1, i);
    S.seg(1, 2, F::FIRST | F::PUB, "dddd");
    fill(0, 3, 1);
    S.oproj(2, 2, 0);
    fill(0, 3, 2);
    S.qproj(2, 3, 0);
    S.handoff_end();
    mixed(0, 3, F::PUB, "dd", 0, nullptr);
    const int pos6[6] = {3, 4, 7, 9, 10, 11};
    nextD[1] = 10;
    mixed(1, 3, F::RF | F::FIRST | F::PUB, "adbhchhAhBhC", 7, pos6);
    S.oproj(3, 3, LD_HIT);
}

typedef CUresult (*EncodeFn)(CUtensorMap*, CUtensorMapDataType, cuuint32_t, void*, const cuuint64_t*,
                             const cuuint64_t*, const cuuint32_t*, const cuuint32_t*, CUtensorMapInterleave,
                             CUtensorMapSwizzle, CUtensorMapL2promotion, CUtensorMapFloatOOBfill);

}

extern "C" void kernel_launch(void* const* d_in, const int* in_sizes, int n_in, void* d_out, int out_size) {
    (void)in_sizes; (void)n_in; (void)out_size;
    Params P;
    void* fn = nullptr;
    cudaDriverEntryPointQueryResult qr;
    cudaGetDriverEntryPoint("cuTensorMapEncodeTiled", &fn, cudaEnableDefault, &qr);
    EncodeFn encode = reinterpret_cast<EncodeFn>(fn);
    auto make_map = [&](int i, void* base, cuuint64_t rows, cuuint64_t rowBytes, cuuint64_t lines, cuuint32_t boxRows,
                        cuuint32_t boxLines) {
        const cuuint64_t dims[3] = {64, rows, lines};
        const cuuint64_t strides[2] = {rowBytes, 128};
        const cuuint32_t box[3] = {64, boxRows, boxLines};
        const cuuint32_t es[3] = {1, 1, 1};
        encode(&P.tm[i], CU_TENSOR_MAP_DATA_TYPE_BFLOAT16, 3, base, dims, strides, box, es, CU_TENSOR_MAP_INTERLEAVE_NONE,
               CU_TENSOR_MAP_SWIZZLE_128B, CU_TENSOR_MAP_L2_PROMOTION_NONE, CU_TENSOR_MAP_FLOAT_OOB_FILL_NONE);
    };
    for (int i = 0; i < 2; i++) {
        void* const* in = d_in + 5 * i;
        make_map(2 * i, in[1], 2 * 32 * 4096, 384, 3, 64, 3);
        make_map(2 * i + 1, in[2], 2 * 32 * 4096, 384, 3, 64, 3);
        make_map(4 + i, in[3], 640, 12288, 96, 64, 3);
        make_map(8 + i, in[3], 640, 12288, 96, 32, 3);
        make_map(6 + i, in[4], 6144, 1280, 10, 16, 10);
    }
    P.x = static_cast<const __nv_bfloat16*>(d_in[0]);
    P.kA = static_cast<const __nv_bfloat16*>(d_in[1]);
    P.out = static_cast<__nv_bfloat16*>(d_out);
    build_schedule(P);
    cudaFuncSetAttribute(fused_decode_kernel, cudaFuncAttributeMaxDynamicSharedMemorySize, kSmemBytes);
    fused_decode_kernel<<<kCtas, kThreads, kSmemBytes>>>(P);
}
```
